```python
import torch

def _softmax(x, axis=-1):
    return torch.softmax(x, dim=axis)
def _gelu(x):
    return torch.nn.functional.gelu(x, approximate="tanh")
def _silu(x):
    return torch.nn.functional.silu(x)
def _sigmoid(x):
    return torch.sigmoid(x)
def _layernorm(x, axis=-1, eps=1e-5):
    m = x.mean(dim=axis, keepdim=True)
    v = x.var(dim=axis, keepdim=True, unbiased=False)
    return (x - m) / torch.sqrt(v + eps)
def _scatter_add(tgt, idx, src, axis=0):
    return tgt.clone().index_add_(axis, idx, src)
def _segment_sum(src, seg, n):
    out = torch.zeros((n,) + src.shape[1:], dtype=src.dtype)
    return out.index_add_(0, seg, src)
def _pad(x, pw):
    flat = tuple(v for pair in reversed(pw) for v in pair)
    return torch.nn.functional.pad(x, flat)

kernel_name = 'interleave_layers__sliding_block_cached__glu_gated_swiglu__decode'

def setup_inputs():

    _w = (lambda a: (lambda t: t.to(torch.bfloat16) if t.is_floating_point() else t)(torch.as_tensor(a)))
    def _A_setup():
        B, Sq, D = 1, 1, 512
        Hq, Hkv, Sk, Dh = 32, 32, 4096, 128
        assert Hq % Hkv == 0, (Hq, Hkv)
        return {
            "x": _w((lambda *s: torch.randn(*s, dtype=torch.bfloat16) * 0.05)(B, Sq, D)),
            "k_cache": _w((lambda *s: torch.randn(*s, dtype=torch.bfloat16) * 0.8)(B, Hkv, Sk, Dh)),
            "v_cache": _w((lambda *s: torch.randn(*s, dtype=torch.bfloat16) * 0.8)(B, Hkv, Sk, Dh)),
            "wq": _w((lambda *s: torch.randn(*s, dtype=torch.bfloat16) * 0.8)(D, Hq * Dh) * (D ** -0.5)),
            "wo": _w((lambda *s: torch.randn(*s, dtype=torch.bfloat16) * 0.8)(Hq * Dh, D) * ((Hq * Dh) ** -0.5)),
        }
    _A_in = _A_setup()

    def _B_setup():
        B, S, D, F = 1, 1, 512, 1376
        return {
            "x": _w((lambda *s: torch.randn(*s, dtype=torch.bfloat16) * 0.05)(B, S, D)),
            "w1": _w((lambda *s: torch.randn(*s, dtype=torch.bfloat16) * 0.2)(D, F) * (2.0 / D) ** 0.5),
            "w3": _w((lambda *s: torch.randn(*s, dtype=torch.bfloat16) * 0.2)(D, F) * (2.0 / D) ** 0.5),
            "w2": _w((lambda *s: torch.randn(*s, dtype=torch.bfloat16) * 0.2)(F, D) * (2.0 / F) ** 0.5),
        }
    _B_in = _B_setup()

    return {
        "A_x": _A_in["x"],
        "A_k_cache": _A_in["k_cache"],
        "A_v_cache": _A_in["v_cache"],
        "A_wq": _A_in["wq"],
        "A_wo": _A_in["wo"],
        "B_x": _B_in["x"],
        "B_w1": _B_in["w1"],
        "B_w3": _B_in["w3"],
        "B_w2": _B_in["w2"],
    }

def reference(A_x, A_k_cache, A_v_cache, A_wq, A_wo, B_x, B_w1, B_w3, B_w2):
    def _A_ref(x, k_cache, v_cache, wq, wo):
        B, Sq, D = x.shape
        Hq, Dh = 32, 128
        Hkv, Sk = k_cache.shape[1], k_cache.shape[2]
        W = min(4096, max(256, Sk // 4))
        rep = Hq // Hkv
        q = (lambda x, *d: x.permute(*d))((x @ wq).reshape(B, Sq, Hq, Dh), 0, 2, 1, 3)
        k = (lambda x, n, axis: torch.repeat_interleave(x, n, dim=axis))(k_cache[:, :, Sk - W:, :], rep, axis=1)
        v = (lambda x, n, axis: torch.repeat_interleave(x, n, dim=axis))(v_cache[:, :, Sk - W:, :], rep, axis=1)
        scores = torch.einsum("bhqd,bhkd->bhqk", q, k) * (Dh ** -0.5)
        p = _softmax(scores, axis=-1)
        o = torch.einsum("bhqk,bhkd->bhqd", p, v)
        return (lambda x, *d: x.permute(*d))(o, 0, 2, 1, 3).reshape(B, Sq, Hq * Dh) @ wo

    def _B_ref(x, w1, w3, w2):
        gate = torch.einsum("bsd,df->bsf", x, w1)
        up = torch.einsum("bsd,df->bsf", x, w3)
        h = _silu(gate) * up
        out = torch.einsum("bsf,fd->bsd", h, w2)
        return out

    x = A_x
    x = x + _A_ref(_layernorm(x, axis=-1), A_k_cache, A_v_cache, A_wq, A_wo)
    x = x + _B_ref(_layernorm(x, axis=-1), B_w1, B_w3, B_w2)
    x = x + _A_ref(_layernorm(x, axis=-1), A_k_cache, A_v_cache, A_wq, A_wo)
    x = x + _B_ref(_layernorm(x, axis=-1), B_w1, B_w3, B_w2)
    return x
```

```cpp
#include <cuda_runtime.h>
#include <cuda_bf16.h>
#include <cuda.h>
#include <stdint.h>

namespace {

constexpr int kD = 512, kHQ = 32, kDH = 128, kSK = 4096, kW = 1024, kF = 1376;
constexpr int kNCTA = 128, kNTHR = 544;

constexpr uint32_t OFF_WQ = 0;
constexpr uint32_t OFF_V = 65536;
constexpr uint32_t OFF_WO = 131072;
constexpr uint32_t OFF_W2 = 163840;
constexpr uint32_t OFF_W1 = 176128;
constexpr uint32_t OFF_W3 = 188416;
constexpr uint32_t OFF_XS = 200704;
constexpr uint32_t OFF_XF = OFF_XS + 512;
constexpr uint32_t OFF_QP = OFF_XF + 512;
constexpr uint32_t OFF_QC = OFF_QP + 1024;
constexpr uint32_t OFF_QS = OFF_QC + 1024;
constexpr uint32_t OFF_OS = OFF_QS + 256;
constexpr uint32_t OFF_SS = OFF_OS + 256;
constexpr uint32_t OFF_HP = OFF_SS + 1152;
constexpr uint32_t OFF_HC = OFF_HP + 1920;
constexpr uint32_t OFF_HS = OFF_HC + 1920;
constexpr uint32_t OFF_RS = OFF_HS + 64;
constexpr uint32_t OFF_MB = OFF_RS + 32;
constexpr uint32_t SMEM_USED = OFF_MB + 128;
constexpr uint32_t SMEM_BYTES = SMEM_USED + 1024;
enum { MB_WQ = 0, MB_V, MB_WO, MB_W13, MB_W2, MB_EX0   };
enum { B_XA = 1, B_XF, B_Q, B_S, B_O, B_H };

__device__ __align__(256) float g_ar_raw[4096 + 4096];
__device__ __align__(256) unsigned long long g_ox[kNCTA * 128];
__device__ __align__(256) unsigned g_epoch_line[64];
__device__ __align__(256) unsigned g_flag_line[64];
__device__ float g_fb[8192];
#define TS(i)

__device__ __forceinline__ uint32_t smem_u32(const void* p) { return (uint32_t)__cvta_generic_to_shared(p); }
__device__ __forceinline__ void mbar_init(uint32_t bar, int cnt) { asm volatile("mbarrier.init.shared::cta.b64 [%0], %1;" :: "r"(bar), "r"(cnt) : "memory"); }
__device__ __forceinline__ void mbar_expect(uint32_t bar, uint32_t bytes) { asm volatile("mbarrier.arrive.expect_tx.shared::cta.b64 _, [%0], %1;" :: "r"(bar), "r"(bytes) : "memory"); }
__device__ __forceinline__ void mbar_arrive(uint32_t bar) { asm volatile("mbarrier.arrive.shared::cta.b64 _, [%0];" :: "r"(bar) : "memory"); }
__device__ __forceinline__ void mbar_wait(uint32_t bar) {
    for (int i = 0; i < (1 << 20); i++) {
        uint32_t ok;
        asm volatile("{\n.reg .pred p;\nmbarrier.try_wait.parity.acquire.cluster.shared::cta.b64 p, [%1], 0;\nselp.u32 %0, 1, 0, p;\n}" : "=r"(ok) : "r"(bar) : "memory");
        if (ok) break;
    }
}
__device__ __forceinline__ void bar_sync(int id, int n) { asm volatile("bar.sync %0, %1;" :: "r"(id), "r"(n) : "memory"); }
__device__ __forceinline__ void bar_arrive(int id, int n) { asm volatile("bar.arrive %0, %1;" :: "r"(id), "r"(n) : "memory"); }
__device__ __forceinline__ void tma2d(uint32_t dst, const CUtensorMap* tm, int c0, int c1, uint32_t bar) {
    asm volatile("cp.async.bulk.tensor.2d.shared::cluster.global.mbarrier::complete_tx::bytes [%0], [%1, {%3, %4}], [%2];"
                 :: "r"(dst), "l"((uint64_t)tm), "r"(bar), "r"(c0), "r"(c1) : "memory");
}
__device__ __forceinline__ void ldsm4t(uint32_t* r, uint32_t addr) {
    asm volatile("ldmatrix.sync.aligned.m8n8.x4.trans.shared.b16 {%0,%1,%2,%3}, [%4];" : "=r"(r[0]), "=r"(r[1]), "=r"(r[2]), "=r"(r[3]) : "r"(addr) : "memory");
}
__device__ __forceinline__ void ldsm2t(uint32_t* r, uint32_t addr) {
    asm volatile("ldmatrix.sync.aligned.m8n8.x2.trans.shared.b16 {%0,%1}, [%2];" : "=r"(r[0]), "=r"(r[1]) : "r"(addr) : "memory");
}
__device__ __forceinline__ void mma16(float* c, uint32_t a0, uint32_t a1, uint32_t a2, uint32_t a3, uint32_t b0, uint32_t b1) {
    asm volatile("mma.sync.aligned.m16n8k16.row.col.f32.bf16.bf16.f32 {%0,%1,%2,%3}, {%4,%5,%6,%7}, {%8,%9}, {%0,%1,%2,%3};"
                 : "+f"(c[0]), "+f"(c[1]), "+f"(c[2]), "+f"(c[3]) : "r"(a0), "r"(a1), "r"(a2), "r"(a3), "r"(b0), "r"(b1));
}
__device__ __forceinline__ void mma8(float* c, uint32_t a0, uint32_t a1, uint32_t b0) {
    asm volatile("mma.sync.aligned.m16n8k8.row.col.f32.bf16.bf16.f32 {%0,%1,%2,%3}, {%4,%5}, {%6}, {%0,%1,%2,%3};"
                 : "+f"(c[0]), "+f"(c[1]), "+f"(c[2]), "+f"(c[3]) : "r"(a0), "r"(a1), "r"(b0));
}
__device__ __forceinline__ uint4 lds128(uint32_t a) { uint4 v; asm volatile("ld.shared.v4.u32 {%0,%1,%2,%3}, [%4];" : "=r"(v.x), "=r"(v.y), "=r"(v.z), "=r"(v.w) : "r"(a) : "memory"); return v; }
__device__ __forceinline__ float4 lds128f(uint32_t a) { float4 v; asm volatile("ld.shared.v4.f32 {%0,%1,%2,%3}, [%4];" : "=f"(v.x), "=f"(v.y), "=f"(v.z), "=f"(v.w) : "r"(a) : "memory"); return v; }
__device__ __forceinline__ float2 lds64f(uint32_t a) { float2 v; asm volatile("ld.shared.v2.f32 {%0,%1}, [%2];" : "=f"(v.x), "=f"(v.y) : "r"(a) : "memory"); return v; }
__device__ __forceinline__ uint32_t lds16(uint32_t a) { uint16_t v; asm volatile("ld.shared.u16 %0, [%1];" : "=h"(v) : "r"(a) : "memory"); return v; }
__device__ __forceinline__ void sts16(uint32_t a, uint32_t v) { asm volatile("st.shared.u16 [%0], %1;" :: "r"(a), "h"((uint16_t)v) : "memory"); }
__device__ __forceinline__ void sts32(uint32_t a, uint32_t v) { asm volatile("st.shared.u32 [%0], %1;" :: "r"(a), "r"(v) : "memory"); }
__device__ __forceinline__ void sts64(uint32_t a, uint32_t v0, uint32_t v1) { asm volatile("st.shared.v2.u32 [%0], {%1,%2};" :: "r"(a), "r"(v0), "r"(v1) : "memory"); }
__device__ __forceinline__ void sts64f(uint32_t a, float v0, float v1) { asm volatile("st.shared.v2.f32 [%0], {%1,%2};" :: "r"(a), "f"(v0), "f"(v1) : "memory"); }
__device__ __forceinline__ void stasync64f(uint32_t a, float v0, float v1, uint32_t bar) {
    asm volatile("st.async.shared::cluster.mbarrier::complete_tx::bytes.v2.f32 [%0], {%1,%2}, [%3];" :: "r"(a), "f"(v0), "f"(v1), "r"(bar) : "memory");
}
__device__ __forceinline__ uint4 ldg_stream(const void* p) {
    uint4 v; asm volatile("ld.global.nc.L1::no_allocate.v4.u32 {%0,%1,%2,%3}, [%4];" : "=r"(v.x), "=r"(v.y), "=r"(v.z), "=r"(v.w) : "l"(p)); return v;
}
__device__ __forceinline__ uint4 ld_poll(const void* p) {
    unsigned long long a, b;
    asm volatile("ld.relaxed.gpu.global.v2.b64 {%0,%1}, [%2];" : "=l"(a), "=l"(b) : "l"(p) : "memory");
    return make_uint4((uint32_t)a, (uint32_t)(a >> 32), (uint32_t)b, (uint32_t)(b >> 32));
}
__device__ __forceinline__ void st_pkt(void* p, uint32_t v, uint32_t tag) {
    unsigned long long a = (unsigned long long)v | ((unsigned long long)tag << 32);
    asm volatile("st.relaxed.gpu.global.b64 [%0], %1;" :: "l"(p), "l"(a) : "memory");
}
__device__ __forceinline__ uint32_t pack_bf16(float lo, float hi) {
    uint32_t r; asm("cvt.rn.bf16x2.f32 %0, %1, %2;" : "=r"(r) : "f"(hi), "f"(lo)); return r;
}
__device__ __forceinline__ float bf_lo(uint32_t v) { return __uint_as_float(v << 16); }
__device__ __forceinline__ float bf_hi(uint32_t v) { return __uint_as_float(v & 0xffff0000u); }
__device__ __forceinline__ float ex2(float x) { float r; asm("ex2.approx.ftz.f32 %0, %1;" : "=f"(r) : "f"(x)); return r; }
__device__ __forceinline__ float warp_max(float v) {
    int i = __float_as_int(v);
    i ^= (i >> 31) & 0x7fffffff;
    i = __reduce_max_sync(0xffffffffu, i);
    i ^= (i >> 31) & 0x7fffffff;
    return __int_as_float(i);
}
__device__ __forceinline__ uint32_t ar_off(int k, int ln) {
    return (ln >> 3) * 4096 + ((ln >> 1) & 3) * 1024 + (ln & 1) * 256 + (k & 1) * 128 + (k >> 1) * 512;
}

__global__ void __cluster_dims__(2, 1, 1) __launch_bounds__(kNTHR, 1)
fused_kernel(const __grid_constant__ CUtensorMap tm_wq, const __grid_constant__ CUtensorMap tm_v,
             const __grid_constant__ CUtensorMap tm_wo, const __grid_constant__ CUtensorMap tm_w1,
             const __grid_constant__ CUtensorMap tm_w3, const __grid_constant__ CUtensorMap tm_w2,
             const __nv_bfloat16* __restrict__ x0, const __nv_bfloat16* __restrict__ kc, __nv_bfloat16* __restrict__ out) {
    extern __shared__ uint8_t smem_raw[];
    const uint32_t sb = (smem_u32(smem_raw) + 1023u) & ~1023u;
    const int tid = threadIdx.x, warp = tid >> 5, lane = tid & 31;
    const int g = lane >> 2, t = lane & 3;
    const int c = blockIdx.x, h = c >> 2, j = c & 3, r = c & 1, p = c >> 1;
    char* const ar = (char*)(((uintptr_t)g_ar_raw + 16383) & ~(uintptr_t)16383);
    uint32_t rsb;
    asm("mapa.shared::cluster.u32 %0, %1, %2;" : "=r"(rsb) : "r"(sb), "r"(r ^ 1));

    if (warp == 16) {
        const int f0 = p < 44 ? 24 * p : 1056 + 16 * (p - 44);
        const int nf = p < 44 ? 24 : 16;
        TS(0);
        if (lane == 0) {
            for (int i = 0; i < 5; i++) mbar_init(sb + OFF_MB + i * 8, 1);
            mbar_init(sb + OFF_MB + (MB_EX0 + 0) * 8, 9);
            mbar_init(sb + OFF_MB + (MB_EX0 + 1) * 8, 13);
            mbar_init(sb + OFF_MB + (MB_EX0 + 2) * 8, 9);
            mbar_init(sb + OFF_MB + (MB_EX0 + 3) * 8, 13);
            asm volatile("fence.mbarrier_init.release.cluster;" ::: "memory");
            mbar_expect(sb + OFF_MB + MB_WQ * 8, 65536);
            tma2d(sb + OFF_WQ, &tm_wq, h * 128, r * 256, sb + OFF_MB + MB_WQ * 8);
            tma2d(sb + OFF_WQ + 32768, &tm_wq, h * 128 + 64, r * 256, sb + OFF_MB + MB_WQ * 8);
            mbar_expect(sb + OFF_MB + MB_V * 8, 65536);
            const int vrow = h * kSK + (kSK - kW) + j * 256;
            tma2d(sb + OFF_V, &tm_v, 0, vrow, sb + OFF_MB + MB_V * 8);
            tma2d(sb + OFF_V + 32768, &tm_v, 64, vrow, sb + OFF_MB + MB_V * 8);
            mbar_expect(sb + OFF_MB + MB_WO * 8, 32768);
            tma2d(sb + OFF_WO, &tm_wo, j * 128, h * 128, sb + OFF_MB + MB_WO * 8);
            tma2d(sb + OFF_WO + 16384, &tm_wo, j * 128 + 64, h * 128, sb + OFF_MB + MB_WO * 8);
            mbar_expect(sb + OFF_MB + MB_W13 * 8, 24576);
            tma2d(sb + OFF_W1, &tm_w1, f0, r * 256, sb + OFF_MB + MB_W13 * 8);
            tma2d(sb + OFF_W3, &tm_w3, f0, r * 256, sb + OFF_MB + MB_W13 * 8);
            mbar_expect(sb + OFF_MB + MB_W2 * 8, 12288);
            for (int i = 0; i < 4; i++) tma2d(sb + OFF_W2 + i * 3072, &tm_w2, r * 256 + i * 64, f0, sb + OFF_MB + MB_W2 * 8);
            mbar_expect(sb + OFF_MB + (MB_EX0 + 0) * 8, 1024 + 8);
            mbar_expect(sb + OFF_MB + (MB_EX0 + 1) * 8, 1536 + 8);
            mbar_expect(sb + OFF_MB + (MB_EX0 + 2) * 8, 512 + 8);
            mbar_expect(sb + OFF_MB + (MB_EX0 + 3) * 8, 768 + 8);
        }
        __syncwarp();
        asm volatile("barrier.cluster.arrive.relaxed.aligned;" ::: "memory");
        unsigned epoch;
        asm volatile("ld.relaxed.gpu.global.u32 %0, [%1];" : "=r"(epoch) : "l"(g_epoch_line) : "memory");
        float xv[8];
#pragma unroll
        for (int i = 0; i < 4; i++) {
            uint32_t v = *(const uint32_t*)(x0 + r * 256 + (4 * i + (lane >> 3)) * 16 + (lane & 7) * 2);
            xv[2 * i] = bf_lo(v); xv[2 * i + 1] = bf_hi(v);
        }
        if (c == 0) {
#pragma unroll 4
            for (int i = 0; i < 32; i++) asm volatile("st.relaxed.gpu.global.v4.u32 [%0], {%1,%1,%1,%1};" :: "l"(ar + i * 512 + lane * 16), "r"(0) : "memory");
            __threadfence();
            __syncwarp();
            if (lane == 0) asm volatile("st.relaxed.gpu.global.u32 [%0], %1;" :: "l"(g_flag_line), "r"(epoch + 1) : "memory");
        }
        if (lane == 0) sts32(sb + OFF_MB + 96, epoch);
        asm volatile("barrier.cluster.wait.acquire.aligned;" ::: "memory");
        const uint32_t xs_a = sb + OFF_XS + ((lane >> 4) & 1) * 64 + (lane & 3) * 16 + ((lane >> 3) & 1) * 8 + ((lane >> 2) & 1) * 4;
        const char* const ar_l = ar + ar_off(0, r * 16 + (lane >> 3)) + (lane & 7) * 16;
        const char* const ox = (const char*)(g_ox + (c & ~3) * 128);
        float cs[4] = {0.f, 0.f, 0.f, 0.f}, c1 = 0.f, c3 = 0.f;

#pragma unroll 1
        for (int st = 0; st < 4; st++) {
            if (st > 0) {
                const float target = (st & 1) ? 32.f : 64.f;
                const char* a = ar_l + ((st - 1) & 1) * 128 + ((st - 1) >> 1) * 512;
                uint4 v0, v1, v2, v3;
                for (int it = 0; it < (1 << 18); it++) {
                    v0 = ld_poll(a); v1 = ld_poll(a + 2048); v2 = ld_poll(a + 4096); v3 = ld_poll(a + 6144);
                    const uint32_t tg = __float_as_uint(target);
                    bool ok = v0.y == tg && v0.w == tg && v1.y == tg && v1.w == tg && v2.y == tg && v2.w == tg && v3.y == tg && v3.w == tg;
                    if (__all_sync(0xffffffffu, ok)) break;
                }
                uint32_t d;
                d = pack_bf16(__uint_as_float(v0.x), __uint_as_float(v0.z)); xv[0] += bf_lo(d); xv[1] += bf_hi(d);
                d = pack_bf16(__uint_as_float(v1.x), __uint_as_float(v1.z)); xv[2] += bf_lo(d); xv[3] += bf_hi(d);
                d = pack_bf16(__uint_as_float(v2.x), __uint_as_float(v2.z)); xv[4] += bf_lo(d); xv[5] += bf_hi(d);
                d = pack_bf16(__uint_as_float(v3.x), __uint_as_float(v3.z)); xv[6] += bf_lo(d); xv[7] += bf_hi(d);
            }
            TS(1 + st * 6);
            uint32_t xp[4];
#pragma unroll
            for (int i = 0; i < 4; i++) { xp[i] = pack_bf16(xv[2 * i], xv[2 * i + 1]); sts32(xs_a + i * 128, xp[i]); }
            if (st & 1) bar_arrive(B_XF, 416); else bar_arrive(B_XA, 288);
            float s1 = 0.f, s2 = 0.f;
#pragma unroll
            for (int i = 0; i < 4; i++) {
                xv[2 * i] = bf_lo(xp[i]); xv[2 * i + 1] = bf_hi(xp[i]);
                s1 += xv[2 * i] + xv[2 * i + 1];
                s2 = fmaf(xv[2 * i], xv[2 * i], s2); s2 = fmaf(xv[2 * i + 1], xv[2 * i + 1], s2);
                sts32(sb + OFF_XF + i * 128 + lane * 4, xp[i]);
            }
#pragma unroll
            for (int o = 16; o > 0; o >>= 1) { s1 += __shfl_xor_sync(0xffffffffu, s1, o); s2 += __shfl_xor_sync(0xffffffffu, s2, o); }
            if (lane == 0) stasync64f(rsb + OFF_RS + st * 8, s1, s2, rsb + OFF_MB + (MB_EX0 + st) * 8);
            mbar_wait(sb + OFF_MB + (MB_EX0 + st) * 8);
            TS(2 + st * 6);
            const float2 rs = lds64f(sb + OFF_RS + st * 8);
            const float mean = (s1 + rs.x) * (1.f / kD);
            const float var = fmaxf((s2 + rs.y) * (1.f / kD) - mean * mean, 0.f);
            const float rstd = rsqrtf(var + 1e-5f);
            if (!(st & 1)) {
                const float4 a = lds128f(sb + OFF_QP + lane * 16), b = lds128f(sb + OFF_QP + 512 + lane * 16);
                if (st == 0) {
                    const float4 u = lds128f(sb + OFF_QC + lane * 16), w = lds128f(sb + OFF_QC + 512 + lane * 16);
                    cs[0] = u.x + w.x; cs[1] = u.y + w.y; cs[2] = u.z + w.z; cs[3] = u.w + w.w;
                }
                const float q0 = rstd * (a.x + b.x - mean * cs[0]), q8 = rstd * (a.y + b.y - mean * cs[1]);
                const float q1 = rstd * (a.z + b.z - mean * cs[2]), q9 = rstd * (a.w + b.w - mean * cs[3]);
                sts32(sb + OFF_QS + g * 32 + t * 4, pack_bf16(q0, q1));
                sts32(sb + OFF_QS + g * 32 + t * 4 + 16, pack_bf16(q8, q9));
                bar_arrive(B_Q, 288);
                const uint32_t tag = epoch * 2 + (st >> 1) + 1;
                if (st == 0) {
                    for (int it = 0; it < (1 << 18); it++) {
                        unsigned fl;
                        asm volatile("ld.acquire.gpu.global.u32 %0, [%1];" : "=r"(fl) : "l"(g_flag_line) : "memory");
                        if (fl == epoch + 1) break;
                    }
                }
                bar_sync(B_S, 544);
                TS(3 + st * 6);
                const float4 sa = lds128f(sb + OFF_SS + lane * 16), sc = lds128f(sb + OFF_SS + 576 + lane * 16);
                const float M = warp_max(fmaxf(fmaxf(fmaxf(sa.x, sa.y), fmaxf(sa.z, sa.w)), fmaxf(fmaxf(sc.x, sc.y), fmaxf(sc.z, sc.w))));
                float L = ((ex2(sa.x - M) + ex2(sa.y - M)) + (ex2(sa.z - M) + ex2(sa.w - M))) + ((ex2(sc.x - M) + ex2(sc.y - M)) + (ex2(sc.z - M) + ex2(sc.w - M)));
#pragma unroll
                for (int o = 16; o > 0; o >>= 1) L += __shfl_xor_sync(0xffffffffu, L, o);
                if (lane < 2) st_pkt(g_ox + c * 128 + 64 + lane, __float_as_uint(lane ? L : M), tag);
                uint4 d0, d1, d2, d3, e0, e1, e2, e3;
                for (int it = 0; it < (1 << 18); it++) {
                    d0 = ld_poll(ox + lane * 16); d1 = ld_poll(ox + 1024 + lane * 16); d2 = ld_poll(ox + 2048 + lane * 16); d3 = ld_poll(ox + 3072 + lane * 16);
                    e0 = ld_poll(ox + 512); e1 = ld_poll(ox + 1024 + 512); e2 = ld_poll(ox + 2048 + 512); e3 = ld_poll(ox + 3072 + 512);
                    bool ok = d0.y == tag && d0.w == tag && d1.y == tag && d1.w == tag && d2.y == tag && d2.w == tag && d3.y == tag && d3.w == tag &&
                              e0.y == tag && e0.w == tag && e1.y == tag && e1.w == tag && e2.y == tag && e2.w == tag && e3.y == tag && e3.w == tag;
                    if (__all_sync(0xffffffffu, ok)) break;
                }
                TS(4 + st * 6);
                const float m0 = __uint_as_float(e0.x), m1 = __uint_as_float(e1.x), m2 = __uint_as_float(e2.x), m3 = __uint_as_float(e3.x);
                const float Mh = fmaxf(fmaxf(m0, m1), fmaxf(m2, m3));
                float a0 = ex2(m0 - Mh), a1 = ex2(m1 - Mh), a2 = ex2(m2 - Mh), a3 = ex2(m3 - Mh);
                const float Lh = (a0 * __uint_as_float(e0.z) + a1 * __uint_as_float(e1.z)) + (a2 * __uint_as_float(e2.z) + a3 * __uint_as_float(e3.z));
                const float il = __frcp_rn(Lh);
                const float o0 = ((a0 * bf_lo(d0.x) + a1 * bf_lo(d1.x)) + (a2 * bf_lo(d2.x) + a3 * bf_lo(d3.x))) * il;
                const float o8 = ((a0 * bf_hi(d0.x) + a1 * bf_hi(d1.x)) + (a2 * bf_hi(d2.x) + a3 * bf_hi(d3.x))) * il;
                const float o1 = ((a0 * bf_lo(d0.z) + a1 * bf_lo(d1.z)) + (a2 * bf_lo(d2.z) + a3 * bf_lo(d3.z))) * il;
                const float o9 = ((a0 * bf_hi(d0.z) + a1 * bf_hi(d1.z)) + (a2 * bf_hi(d2.z) + a3 * bf_hi(d3.z))) * il;
                sts64(sb + OFF_OS + (g >> 1) * 64 + t * 16 + (g & 1) * 8, pack_bf16(o0, o1), pack_bf16(o8, o9));
                bar_arrive(B_O, 288);
                TS(5 + st * 6);
            } else {
                const uint32_t ha = sb + OFF_HP + min(lane, 23) * 80;
                const float4 a = lds128f(ha), b = lds128f(ha + 16), d = lds128f(ha + 32), e = lds128f(ha + 48);
                if (st == 1) {
                    const float4 a_ = lds128f(ha + 1920), b_ = lds128f(ha + 1920 + 16), d_ = lds128f(ha + 1920 + 32), e_ = lds128f(ha + 1920 + 48);
                    c1 = ((a_.x + a_.z) + (b_.x + b_.z)) + ((d_.x + d_.z) + (e_.x + e_.z));
                    c3 = ((a_.y + a_.w) + (b_.y + b_.w)) + ((d_.y + d_.w) + (e_.y + e_.w));
                }
                const float G = ((a.x + a.z) + (b.x + b.z)) + ((d.x + d.z) + (e.x + e.z));
                const float U = ((a.y + a.w) + (b.y + b.w)) + ((d.y + d.w) + (e.y + e.w));
                const float gate = rstd * (G - mean * c1), up = rstd * (U - mean * c3);
                float hv = __fdividef(gate, 1.f + ex2(-1.4426950408889634f * gate)) * up;
                if (lane >= nf) hv = 0.f;
                sts16(sb + OFF_HS + ((lane & 7) >> 1) * 16 + (lane >> 4) * 8 + ((lane >> 3) & 1) * 4 + (lane & 1) * 2, pack_bf16(hv, 0.f));
                bar_arrive(B_H, 544);
                TS(3 + st * 6);
            }
        }
        return;
    }

    uint32_t R[64];
    uint32_t S[32];
    if (warp < 8) {
        const char* kp = (const char*)(kc + ((size_t)h * kSK + (kSK - kW) + j * 256 + warp * 32 + g) * kDH) + t * 16;
#pragma unroll
        for (int rr = 0; rr < 4; rr++)
#pragma unroll
            for (int i = 0; i < 4; i++) {
                const uint4 v = ldg_stream(kp + rr * 2048 + i * 64);
                R[rr * 16 + i * 4 + 0] = v.x; R[rr * 16 + i * 4 + 1] = v.y; R[rr * 16 + i * 4 + 2] = v.z; R[rr * 16 + i * 4 + 3] = v.w;
            }
    }
    asm volatile("barrier.cluster.arrive.relaxed.aligned;" ::: "memory");
    asm volatile("barrier.cluster.wait.acquire.aligned;" ::: "memory");

    const uint32_t lm_off = ((lane >> 4) * 8 + (lane & 7)) * 128 + ((((warp & 3) * 2 + ((lane >> 3) & 1)) ^ (lane & 7)) << 4);
    const uint32_t ones = 0x3F803F80u;
    const bool odd_g = g & 1;

#pragma unroll 1
    for (int layer = 0; layer < 2; layer++) {
        if (warp < 8) {
            bar_sync(B_Q, 288);
            float a0[4] = {0.f, 0.f, 0.f, 0.f}, a1[4] = {0.f, 0.f, 0.f, 0.f};
#pragma unroll
            for (int i = 0; i < 4; i++) {
                const uint4 b = lds128(sb + OFF_QS + i * 64 + t * 16);
                mma16(a0, R[i * 4 + 0], R[16 + i * 4 + 0], R[i * 4 + 1], R[16 + i * 4 + 1], b.x, b.y);
                mma16(a1, R[32 + i * 4 + 0], R[48 + i * 4 + 0], R[32 + i * 4 + 1], R[48 + i * 4 + 1], b.x, b.y);
                mma16(a0, R[i * 4 + 2], R[16 + i * 4 + 2], R[i * 4 + 3], R[16 + i * 4 + 3], b.z, b.w);
                mma16(a1, R[32 + i * 4 + 2], R[48 + i * 4 + 2], R[32 + i * 4 + 3], R[48 + i * 4 + 3], b.z, b.w);
            }
            const float sv = (t & 2) ? ((t & 1) ? a1[2] : a1[0]) : ((t & 1) ? a0[2] : a0[0]);
            sts32(sb + OFF_SS + (t >> 1) * 576 + (warp * 4 + (g >> 1)) * 16 + (t & 1) * 8 + (g & 1) * 4,
                  __float_as_uint(sv * (0.08838834764831845f * 1.4426950408889634f)));
            bar_arrive(B_S, 544);
            mbar_wait(sb + OFF_MB + MB_WO * 8);
#pragma unroll
            for (int s = 0; s < 8; s++) ldsm4t(&S[s * 4], sb + OFF_WO + (warp >> 2) * 16384 + s * 2048 + lm_off);
            bar_sync(B_O, 288);
#pragma unroll
            for (int i = 0; i < 4; i++) { a0[i] = 0.f; a1[i] = 0.f; }
#pragma unroll
            for (int i = 0; i < 4; i++) {
                const uint4 b = lds128(sb + OFF_OS + i * 64 + t * 16);
                mma16(a0, S[i * 8 + 0], S[i * 8 + 1], S[i * 8 + 2], S[i * 8 + 3], b.x, b.y);
                mma16(a1, S[i * 8 + 4], S[i * 8 + 5], S[i * 8 + 6], S[i * 8 + 7], b.z, b.w);
            }
            if (t < 2) {
                const float v = t ? a0[2] + a1[2] : a0[0] + a1[0];
                asm volatile("red.relaxed.gpu.global.add.v2.f32 [%0], {%1,%2};"
                             :: "l"(ar + ar_off(layer * 2, j * 8 + warp) + (g + 8 * t) * 8), "f"(v), "f"(1.f) : "memory");
            }
        } else {
            const uint32_t wbox = ((warp >> 2) & 1) * 32768 + lm_off;
            mbar_wait(sb + OFF_MB + MB_WQ * 8);
#pragma unroll
            for (int s = 0; s < 16; s++) ldsm4t(&R[s * 4], sb + OFF_WQ + s * 2048 + wbox);
            bar_sync(B_XA, 288);
            float a0[4] = {0.f, 0.f, 0.f, 0.f}, a1[4] = {0.f, 0.f, 0.f, 0.f};
#pragma unroll
            for (int i = 0; i < 8; i++) {
                uint4 b = lds128(sb + OFF_XS + i * 64 + t * 16);
                if (odd_g) b = make_uint4(ones, ones, ones, ones);
                mma16(a0, R[i * 8 + 0], R[i * 8 + 1], R[i * 8 + 2], R[i * 8 + 3], b.x, b.y);
                mma16(a1, R[i * 8 + 4], R[i * 8 + 5], R[i * 8 + 6], R[i * 8 + 7], b.z, b.w);
            }
            {
                const float v0 = (t & 2) ? a0[1] + a1[1] : a0[0] + a1[0];
                const float v1 = (t & 2) ? a0[3] + a1[3] : a0[2] + a1[2];
                const uint32_t off = OFF_QP + (t >> 1) * 1024 + r * 512 + (warp - 8) * 64 + g * 8;
                if (t < 2 || layer == 0) {
                    if (t & 1) stasync64f(rsb + off, v0, v1, rsb + OFF_MB + (MB_EX0 + layer * 2) * 8);
                    else sts64f(sb + off, v0, v1);
                }
                __syncwarp();
                if (lane == 0) mbar_arrive(sb + OFF_MB + (MB_EX0 + layer * 2) * 8);
            }
            mbar_wait(sb + OFF_MB + MB_V * 8);
#pragma unroll
            for (int s = 0; s < 16; s++) ldsm4t(&R[s * 4], sb + OFF_V + s * 2048 + wbox);
            uint32_t tag;
            asm volatile("ld.shared.u32 %0, [%1];" : "=r"(tag) : "r"(sb + OFF_MB + 96) : "memory");
            tag = tag * 2 + layer + 1;
            bar_sync(B_S, 544);
            const float4 sa = lds128f(sb + OFF_SS + lane * 16), sc = lds128f(sb + OFF_SS + 576 + lane * 16);
            const float M = warp_max(fmaxf(fmaxf(fmaxf(sa.x, sa.y), fmaxf(sa.z, sa.w)), fmaxf(fmaxf(sc.x, sc.y), fmaxf(sc.z, sc.w))));
            const uint32_t p0 = pack_bf16(ex2(sa.x - M), ex2(sa.y - M)), p1 = pack_bf16(ex2(sa.z - M), ex2(sa.w - M));
            const uint32_t p2 = pack_bf16(ex2(sc.x - M), ex2(sc.y - M)), p3 = pack_bf16(ex2(sc.z - M), ex2(sc.w - M));
#pragma unroll
            for (int i = 0; i < 4; i++) { a0[i] = 0.f; a1[i] = 0.f; }
#pragma unroll
            for (int i = 0; i < 8; i++) {
                const bool s = g == i;
                mma16(a0, R[i * 8 + 0], R[i * 8 + 1], R[i * 8 + 2], R[i * 8 + 3], s ? p0 : 0u, s ? p1 : 0u);
                mma16(a1, R[i * 8 + 4], R[i * 8 + 5], R[i * 8 + 6], R[i * 8 + 7], s ? p2 : 0u, s ? p3 : 0u);
            }
            float ol = (a0[0] + a0[1]) + (a1[0] + a1[1]), oh = (a0[2] + a0[3]) + (a1[2] + a1[3]);
            ol += __shfl_xor_sync(0xffffffffu, ol, 1); oh += __shfl_xor_sync(0xffffffffu, oh, 1);
            ol += __shfl_xor_sync(0xffffffffu, ol, 2); oh += __shfl_xor_sync(0xffffffffu, oh, 2);
            if (t == 0) st_pkt(g_ox + c * 128 + (warp - 8) * 8 + g, pack_bf16(ol, oh), tag);
        }

        if (warp >= 4) {
            const int mt = (warp - 4) % 3, kq = (warp - 4) / 3;
            mbar_wait(sb + OFF_MB + MB_W13 * 8);
            const uint32_t wa = sb + OFF_W1 + ((lane >> 3) & 1) * 12288 + (kq * 64 + (lane >> 4) * 8 + (lane & 7)) * 48 + mt * 16;
#pragma unroll
            for (int s = 0; s < 4; s++) ldsm4t(&S[s * 4], wa + s * 768);
            bar_sync(B_XF, 416);
            float a0[4] = {0.f, 0.f, 0.f, 0.f}, a1[4] = {0.f, 0.f, 0.f, 0.f};
#pragma unroll
            for (int i = 0; i < 2; i++) {
                uint4 b = lds128(sb + OFF_XS + (kq * 2 + i) * 64 + t * 16);
                if (odd_g) b = make_uint4(ones, ones, ones, ones);
                mma16(a0, S[i * 8 + 0], S[i * 8 + 1], S[i * 8 + 2], S[i * 8 + 3], b.x, b.y);
                mma16(a1, S[i * 8 + 4], S[i * 8 + 5], S[i * 8 + 6], S[i * 8 + 7], b.z, b.w);
            }
            const float v0 = (t & 2) ? a0[1] + a1[1] : a0[0] + a1[0];
            const float v1 = (t & 2) ? a0[3] + a1[3] : a0[2] + a1[2];
            const uint32_t off = OFF_HP + (t >> 1) * 1920 + (mt * 8 + g) * 80 + (r * 4 + kq) * 8;
            if (t < 2 || layer == 0) {
                if (t & 1) stasync64f(rsb + off, v0, v1, rsb + OFF_MB + (MB_EX0 + layer * 2 + 1) * 8);
                else sts64f(sb + off, v0, v1);
            }
            __syncwarp();
            if (lane == 0) mbar_arrive(sb + OFF_MB + (MB_EX0 + layer * 2 + 1) * 8);
        }
        {
            mbar_wait(sb + OFF_MB + MB_W2 * 8);
            const uint32_t wa = sb + OFF_W2 + (warp >> 2) * 3072 + lm_off;
            ldsm4t(&S[16], wa);
            ldsm2t(&S[20], wa + 2048 - (lane >> 4) * 1024);
            char* const ap = ar + ar_off(layer * 2 + 1, r * 16 + warp) + (g + 8 * (t & 1)) * 8;
            bar_sync(B_H, 544);
            const uint4 b = lds128(sb + OFF_HS + t * 16);
            const float xres = __uint_as_float(lds16(sb + OFF_XF + (warp * 16 + g + 8 * (t & 1)) * 2) << 16);
            float a0[4] = {0.f, 0.f, 0.f, 0.f}, a1[4] = {0.f, 0.f, 0.f, 0.f};
            mma16(a0, S[16], S[17], S[18], S[19], b.x, b.y);
            mma8(a1, S[20], S[21], b.z);
            if (t < 2) {
                const float v = t ? a0[2] + a1[2] : a0[0] + a1[0];
                if (layer == 0) {
                    asm volatile("red.relaxed.gpu.global.add.v2.f32 [%0], {%1,%2};" :: "l"(ap), "f"(v), "f"(1.f) : "memory");
                } else {
                    float ov, oc;
                    asm volatile("atom.relaxed.gpu.global.add.v2.f32 {%0,%1}, [%2], {%3,%4};" : "=f"(ov), "=f"(oc) : "l"(ap), "f"(v), "f"(1.f) : "memory");
                    if (oc == 63.f) {
                        const float y = xres + bf_lo(pack_bf16(ov + v, 0.f));
                        const int col = r * 256 + warp * 16 + g + 8 * t;
                        *(uint16_t*)(out + col) = (uint16_t)pack_bf16(y, 0.f);
                        if (col == 0) {
                            uint32_t e;
                            asm volatile("ld.shared.u32 %0, [%1];" : "=r"(e) : "r"(sb + OFF_MB + 96) : "memory");
                            asm volatile("st.relaxed.gpu.global.u32 [%0], %1;" :: "l"(g_epoch_line), "r"(e + 1) : "memory");
                        }
                    }
                }
            }
        }
    }
}

__device__ __forceinline__ float bfr(float v) { return __bfloat162float(__float2bfloat16(v)); }
__global__ void fb_ln(const __nv_bfloat16* x0, int first) {
    __shared__ float red[2][16];
    const int tid = threadIdx.x;
    float x = first ? __bfloat162float(x0[tid]) : g_fb[tid];
    g_fb[tid] = x;
    float s = x;
    for (int o = 16; o > 0; o >>= 1) s += __shfl_xor_sync(0xffffffffu, s, o);
    if ((tid & 31) == 0) red[0][tid >> 5] = s;
    __syncthreads();
    float m = 0.f;
    for (int i = 0; i < 16; i++) m += red[0][i];
    m *= 1.f / kD;
    float d = (x - m) * (x - m);
    for (int o = 16; o > 0; o >>= 1) d += __shfl_xor_sync(0xffffffffu, d, o);
    if ((tid & 31) == 0) red[1][tid >> 5] = d;
    __syncthreads();
    float v = 0.f;
    for (int i = 0; i < 16; i++) v += red[1][i];
    g_fb[512 + tid] = (x - m) * rsqrtf(v * (1.f / kD) + 1e-5f);
}
__global__ void fb_attn(const __nv_bfloat16* kc, const __nv_bfloat16* vc, const __nv_bfloat16* wq) {
    __shared__ float q[128], s[1024], red[32];
    const int h = blockIdx.x, tid = threadIdx.x;
    if (tid < 128) {
        float a = 0.f;
        for (int d = 0; d < kD; d++) a += g_fb[512 + d] * __bfloat162float(wq[(size_t)d * 4096 + h * 128 + tid]);
        q[tid] = bfr(a);
    }
    __syncthreads();
    const __nv_bfloat16* kr = kc + ((size_t)h * kSK + (kSK - kW) + tid) * kDH;
    float a = 0.f;
    for (int d = 0; d < kDH; d++) a += q[d] * __bfloat162float(kr[d]);
    a *= 0.08838834764831845f;
    float m = a;
    for (int o = 16; o > 0; o >>= 1) m = fmaxf(m, __shfl_xor_sync(0xffffffffu, m, o));
    if ((tid & 31) == 0) red[tid >> 5] = m;
    __syncthreads();
    for (int i = 0; i < 32; i++) m = fmaxf(m, red[i]);
    __syncthreads();
    const float e = expf(a - m);
    s[tid] = e;
    float l = e;
    for (int o = 16; o > 0; o >>= 1) l += __shfl_xor_sync(0xffffffffu, l, o);
    if ((tid & 31) == 0) red[tid >> 5] = l;
    __syncthreads();
    l = 0.f;
    for (int i = 0; i < 32; i++) l += red[i];
    if (tid < 128) {
        float o = 0.f;
        const __nv_bfloat16* vr = vc + ((size_t)h * kSK + (kSK - kW)) * kDH + tid;
        for (int k = 0; k < kW; k++) o += s[k] * __bfloat162float(vr[(size_t)k * kDH]);
        g_fb[1024 + h * 128 + tid] = bfr(o / l);
    }
}
__global__ void fb_up(const __nv_bfloat16* w1, const __nv_bfloat16* w3) {
    const int f = blockIdx.x * blockDim.x + threadIdx.x;
    if (f >= kF) return;
    float a = 0.f, b = 0.f;
    for (int d = 0; d < kD; d++) { a += g_fb[512 + d] * __bfloat162float(w1[(size_t)d * kF + f]); b += g_fb[512 + d] * __bfloat162float(w3[(size_t)d * kF + f]); }
    g_fb[5120 + f] = bfr(a / (1.f + expf(-a)) * b);
}
__global__ void fb_down(const __nv_bfloat16* w, int src, int n, __nv_bfloat16* out) {
    const int col = blockIdx.x * blockDim.x + threadIdx.x;
    float a = 0.f;
    for (int k = 0; k < n; k++) a += g_fb[src + k] * __bfloat162float(w[(size_t)k * kD + col]);
    const float y = bfr(g_fb[col] + bfr(a));
    g_fb[col] = y;
    if (out) out[col] = __float2bfloat16(y);
}

typedef CUresult (*EncodeFn)(CUtensorMap*, CUtensorMapDataType, cuuint32_t, void*, const cuuint64_t*, const cuuint64_t*,
                             const cuuint32_t*, const cuuint32_t*, CUtensorMapInterleave, CUtensorMapSwizzle,
                             CUtensorMapL2promotion, CUtensorMapFloatOOBfill);

bool make_map(EncodeFn fn, CUtensorMap* m, const void* base, uint64_t cols, uint64_t rows, uint32_t bc, uint32_t br, bool swz,
              CUtensorMapL2promotion prom) {
    cuuint64_t dims[2] = {cols, rows};
    cuuint64_t strides[1] = {cols * 2};
    cuuint32_t box[2] = {bc, br};
    cuuint32_t es[2] = {1, 1};
    return fn(m, CU_TENSOR_MAP_DATA_TYPE_BFLOAT16, 2, const_cast<void*>(base), dims, strides, box, es, CU_TENSOR_MAP_INTERLEAVE_NONE,
              swz ? CU_TENSOR_MAP_SWIZZLE_128B : CU_TENSOR_MAP_SWIZZLE_NONE, prom, CU_TENSOR_MAP_FLOAT_OOB_FILL_NONE) == CUDA_SUCCESS;
}

}

extern "C" void kernel_launch(void* const* d_in, const int* in_sizes, int n_in, void* d_out, int out_size) {
    (void)in_sizes; (void)n_in; (void)out_size;
    const __nv_bfloat16* x0 = (const __nv_bfloat16*)d_in[0];
    const __nv_bfloat16* kc = (const __nv_bfloat16*)d_in[1];
    const __nv_bfloat16* vc = (const __nv_bfloat16*)d_in[2];
    const __nv_bfloat16* wq = (const __nv_bfloat16*)d_in[3];
    const __nv_bfloat16* wo = (const __nv_bfloat16*)d_in[4];
    const __nv_bfloat16* w1 = (const __nv_bfloat16*)d_in[6];
    const __nv_bfloat16* w3 = (const __nv_bfloat16*)d_in[7];
    const __nv_bfloat16* w2 = (const __nv_bfloat16*)d_in[8];
    __nv_bfloat16* out = (__nv_bfloat16*)d_out;
    cudaStream_t s = cudaStreamPerThread;

    static int state = 0;
    static EncodeFn enc = nullptr;
    if (state == 0) {
        state = 2;
        void* fn = nullptr;
        cudaDriverEntryPointQueryResult qr;
        if (cudaGetDriverEntryPoint("cuTensorMapEncodeTiled", &fn, cudaEnableDefault, &qr) == cudaSuccess && fn &&
            cudaFuncSetAttribute(fused_kernel, cudaFuncAttributeMaxDynamicSharedMemorySize, SMEM_BYTES) == cudaSuccess) {
            enc = (EncodeFn)fn;
            cudaLaunchConfig_t cfg = {};
            cfg.gridDim = dim3(kNCTA); cfg.blockDim = dim3(kNTHR); cfg.dynamicSmemBytes = SMEM_BYTES;
            cudaLaunchAttribute at[1];
            at[0].id = cudaLaunchAttributeClusterDimension;
            at[0].val.clusterDim.x = 2; at[0].val.clusterDim.y = 1; at[0].val.clusterDim.z = 1;
            cfg.attrs = at; cfg.numAttrs = 1;
            int ncl = 0;
            if (cudaOccupancyMaxActiveClusters(&ncl, fused_kernel, &cfg) == cudaSuccess && ncl >= kNCTA / 2) state = 1;
        }
        (void)cudaGetLastError();
    }
    if (state == 1) {
        CUtensorMap m_wq, m_v, m_wo, m_w1, m_w3, m_w2;
        const CUtensorMapL2promotion P = CU_TENSOR_MAP_L2_PROMOTION_L2_256B;
        bool ok = make_map(enc, &m_wq, wq, 4096, 512, 64, 256, true, P) &&
                  make_map(enc, &m_v, vc, 128, (uint64_t)kHQ * kSK, 64, 256, true, P) &&
                  make_map(enc, &m_wo, wo, 512, 4096, 64, 128, true, P) &&
                  make_map(enc, &m_w1, w1, kF, 512, 24, 256, false, CU_TENSOR_MAP_L2_PROMOTION_L2_128B) &&
                  make_map(enc, &m_w3, w3, kF, 512, 24, 256, false, CU_TENSOR_MAP_L2_PROMOTION_L2_128B) &&
                  make_map(enc, &m_w2, w2, 512, kF, 64, 24, true, P);
        if (ok) {
            fused_kernel<<<kNCTA, kNTHR, SMEM_BYTES, s>>>(m_wq, m_v, m_wo, m_w1, m_w3, m_w2, x0, kc, out);
            return;
        }
    }
    for (int layer = 0; layer < 2; layer++) {
        fb_ln<<<1, 512, 0, s>>>(x0, layer == 0);
        fb_attn<<<kHQ, 1024, 0, s>>>(kc, vc, wq);
        fb_down<<<8, 64, 0, s>>>(wo, 1024, 4096, nullptr);
        fb_ln<<<1, 512, 0, s>>>(x0, 0);
        fb_up<<<(kF + 63) / 64, 64, 0, s>>>(w1, w3);
        fb_down<<<8, 64, 0, s>>>(w2, 5120, kF, layer == 1 ? out : nullptr);
    }
}
```

```cpp
#include <cuda_runtime.h>
#include <cuda_bf16.h>
#include <cuda.h>
#include <stdint.h>

namespace {

constexpr int kD = 512, kHQ = 32, kDH = 128, kSK = 4096, kW = 1024, kF = 1376;
constexpr int kNCTA = 128, kNTHR = 384;
constexpr int kNFFN = 43;

struct Sched {
    int tq[4];
    int id[11];
    int t[11];
    int dar[4];
};

constexpr uint32_t OFF_WQ = 0;
constexpr uint32_t OFF_WO = 65536;
constexpr uint32_t OFF_W2 = 131072;
constexpr uint32_t OFF_W1 = 147456;
constexpr uint32_t OFF_W3 = 163840;
constexpr uint32_t OFF_V = OFF_W2;
constexpr uint32_t OFF_XS = 196608;
constexpr uint32_t OFF_ONE = OFF_XS + 576;
constexpr uint32_t OFF_XF = OFF_XS + 1152;
constexpr uint32_t OFF_QP = OFF_XF + 512;
constexpr uint32_t OFF_HP = OFF_QP + 2048;
constexpr uint32_t OFF_OP = OFF_HP + 2048;
constexpr uint32_t OFF_QS = OFF_OP + 1024;
constexpr uint32_t OFF_OS = OFF_QS + 256;
constexpr uint32_t OFF_PS = OFF_OS + 256;
constexpr uint32_t OFF_ZP = OFF_PS + 576;
constexpr uint32_t OFF_MS = OFF_ZP + 576;
constexpr uint32_t OFF_HS = OFF_MS + 64;
constexpr uint32_t OFF_RS = OFF_HS + 64;
constexpr uint32_t OFF_MC = OFF_RS + 256;
constexpr uint32_t OFF_PHI = OFF_MC + 32;
constexpr uint32_t OFF_EP = OFF_PHI + 16;
constexpr uint32_t OFF_DL = OFF_EP + 16;
constexpr uint32_t OFF_MB = OFF_DL + 16;
constexpr uint32_t OFF_TAB = OFF_MB + 256;
constexpr uint32_t SMEM_USED = OFF_TAB + 12288;
constexpr uint32_t SMEM_BYTES = SMEM_USED + 1024 + 256;
enum { MB_K = 0, MB_KFREE, MB_VFREE, MB_WQ, MB_V0  , MB_WO0 = MB_V0 + 4  , MB_W130 = MB_WO0 + 4  , MB_W2 = MB_W130 + 2,
       MB_EX0  , MB_OX0 = MB_EX0 + 4  , MB_MC0 = MB_OX0 + 2  , MB_AL0 = MB_MC0 + 2  , MB_COUNT = MB_AL0 + 2 };
enum { B_X = 1, B_Q, B_S, B_O, B_H, B_RED, B_ST };

__device__ __align__(256) float g_ar_raw[8192 + 8192];
__device__ __align__(256) unsigned g_epoch_line[64];
__device__ __align__(256) unsigned g_flag_line[64];
__device__ float g_fb[8192];
#define TS(i)
#define TW(i)
#define TWD(i, dep)

__device__ __forceinline__ uint32_t smem_u32(const void* p) { return (uint32_t)__cvta_generic_to_shared(p); }
__device__ __forceinline__ void mbar_init(uint32_t bar, int cnt) { asm volatile("mbarrier.init.shared::cta.b64 [%0], %1;" :: "r"(bar), "r"(cnt) : "memory"); }
__device__ __forceinline__ void mbar_expect(uint32_t bar, uint32_t bytes) { asm volatile("mbarrier.arrive.expect_tx.shared::cta.b64 _, [%0], %1;" :: "r"(bar), "r"(bytes) : "memory"); }
__device__ __forceinline__ void mbar_arrive(uint32_t bar) { asm volatile("mbarrier.arrive.shared::cta.b64 _, [%0];" :: "r"(bar) : "memory"); }
__device__ __forceinline__ void mbar_wait(uint32_t bar) {
    for (int i = 0; i < (1 << 20); i++) {
        uint32_t ok;
        asm volatile("{\n.reg .pred p;\nmbarrier.try_wait.parity.shared::cta.b64 p, [%1], 0;\nselp.u32 %0, 1, 0, p;\n}" : "=r"(ok) : "r"(bar) : "memory");
        if (ok) break;
    }
}
__device__ __forceinline__ void bar_sync(int id, int n) { asm volatile("bar.sync %0, %1;" :: "r"(id), "r"(n) : "memory"); }
__device__ __forceinline__ void bar_arrive(int id, int n) { asm volatile("bar.arrive %0, %1;" :: "r"(id), "r"(n) : "memory"); }
__device__ __forceinline__ void tma2d(uint32_t dst, const CUtensorMap* tm, int c0, int c1, uint32_t bar) {
    asm volatile("cp.async.bulk.tensor.2d.shared::cluster.global.mbarrier::complete_tx::bytes [%0], [%1, {%3, %4}], [%2];"
                 :: "r"(dst), "l"((uint64_t)tm), "r"(bar), "r"(c0), "r"(c1) : "memory");
}
__device__ __forceinline__ void ldsm4t(uint32_t* r, uint32_t addr) {
    asm volatile("ldmatrix.sync.aligned.m8n8.x4.trans.shared.b16 {%0,%1,%2,%3}, [%4];" : "=r"(r[0]), "=r"(r[1]), "=r"(r[2]), "=r"(r[3]) : "r"(addr) : "memory");
}
__device__ __forceinline__ void mma16(float* c, uint32_t a0, uint32_t a1, uint32_t a2, uint32_t a3, uint32_t b0, uint32_t b1) {
    asm volatile("mma.sync.aligned.m16n8k16.row.col.f32.bf16.bf16.f32 {%0,%1,%2,%3}, {%4,%5,%6,%7}, {%8,%9}, {%0,%1,%2,%3};"
                 : "+f"(c[0]), "+f"(c[1]), "+f"(c[2]), "+f"(c[3]) : "r"(a0), "r"(a1), "r"(a2), "r"(a3), "r"(b0), "r"(b1));
}
__device__ __forceinline__ uint4 lds128(uint32_t a) { uint4 v; asm volatile("ld.shared.v4.u32 {%0,%1,%2,%3}, [%4];" : "=r"(v.x), "=r"(v.y), "=r"(v.z), "=r"(v.w) : "r"(a) : "memory"); return v; }
__device__ __forceinline__ float4 lds128f(uint32_t a) { float4 v; asm volatile("ld.shared.v4.f32 {%0,%1,%2,%3}, [%4];" : "=f"(v.x), "=f"(v.y), "=f"(v.z), "=f"(v.w) : "r"(a) : "memory"); return v; }
__device__ __forceinline__ float2 lds64f(uint32_t a) { float2 v; asm volatile("ld.shared.v2.f32 {%0,%1}, [%2];" : "=f"(v.x), "=f"(v.y) : "r"(a) : "memory"); return v; }
__device__ __forceinline__ void sts16(uint32_t a, uint32_t v) { asm volatile("st.shared.u16 [%0], %1;" :: "r"(a), "h"((uint16_t)v) : "memory"); }
__device__ __forceinline__ void sts32(uint32_t a, uint32_t v) { asm volatile("st.shared.u32 [%0], %1;" :: "r"(a), "r"(v) : "memory"); }
__device__ __forceinline__ void sts64(uint32_t a, uint32_t v0, uint32_t v1) { asm volatile("st.shared.v2.u32 [%0], {%1,%2};" :: "r"(a), "r"(v0), "r"(v1) : "memory"); }
__device__ __forceinline__ void sts64f(uint32_t a, float v0, float v1) { asm volatile("st.shared.v2.f32 [%0], {%1,%2};" :: "r"(a), "f"(v0), "f"(v1) : "memory"); }
__device__ __forceinline__ void stasync64f(uint32_t a, float v0, float v1, uint32_t bar) {
    asm volatile("st.async.shared::cluster.mbarrier::complete_tx::bytes.v2.f32 [%0], {%1,%2}, [%3];" :: "r"(a), "f"(v0), "f"(v1), "r"(bar) : "memory");
}
__device__ __forceinline__ void send_pair(uint32_t a, uint32_t rbar, float v0, float v1, uint32_t mode) {
    asm volatile("{\n.reg .pred pl, pr;\nsetp.eq.u32 pl, %4, 1;\nsetp.eq.u32 pr, %4, 2;\n"
                 "@pr st.async.shared::cluster.mbarrier::complete_tx::bytes.v2.f32 [%0], {%1,%2}, [%3];\n"
                 "@pl st.shared.v2.f32 [%0], {%1,%2};\n}" :: "r"(a), "f"(v0), "f"(v1), "r"(rbar), "r"(mode) : "memory");
}
__device__ __forceinline__ void red_pair(const void* p, float v, uint32_t on) {
    asm volatile("{\n.reg .pred p;\nsetp.ne.u32 p, %3, 0;\n@p red.relaxed.gpu.global.add.v2.f32 [%0], {%1,%2};\n}" :: "l"(p), "f"(v), "f"(1.f), "r"(on) : "memory");
}
__device__ __forceinline__ float fsel(bool p, float a, float b) { float r; asm("{\n.reg .pred q;\nsetp.ne.u32 q, %3, 0;\nselp.f32 %0, %1, %2, q;\n}" : "=f"(r) : "f"(a), "f"(b), "r"((uint32_t)p)); return r; }
__device__ __forceinline__ void sts128(uint32_t a, uint32_t x, uint32_t y, uint32_t z, uint32_t w) { asm volatile("st.shared.v4.u32 [%0], {%1,%2,%3,%4};" :: "r"(a), "r"(x), "r"(y), "r"(z), "r"(w) : "memory"); }
__device__ __forceinline__ uint32_t lds32(uint32_t a) { uint32_t v; asm volatile("ld.shared.u32 %0, [%1];" : "=r"(v) : "r"(a) : "memory"); return v; }
__device__ __forceinline__ float rsq(float x) { float r; asm("rsqrt.approx.ftz.f32 %0, %1;" : "=f"(r) : "f"(x)); return r; }
__device__ __forceinline__ const char* mk64(uint32_t lo, uint32_t hi) { return (const char*)(((uint64_t)hi << 32) | lo); }
#define PIN32(x) asm volatile("" : "+r"(x))
#define PIN64(x) asm volatile("" : "+l"(x))
#define PINF(x) asm volatile("" : "+f"(x))
__device__ __forceinline__ void bulk_g2s(uint32_t dst, const void* src, uint32_t bytes, uint32_t bar) {
    asm volatile("cp.async.bulk.shared::cluster.global.mbarrier::complete_tx::bytes [%0], [%1], %2, [%3];" :: "r"(dst), "l"(src), "r"(bytes), "r"(bar) : "memory");
}
__device__ __forceinline__ unsigned gtime() { unsigned t; asm volatile("mov.u32 %0, %%globaltimer_lo;" : "=r"(t)); return t; }
__device__ __forceinline__ unsigned clk() { unsigned t; asm volatile("mov.u32 %0, %%clock;" : "=r"(t)); return t; }
__device__ __forceinline__ void spin(int n) { const unsigned t = clk(); while ((int)(clk() - t) < n) {} }
__device__ __forceinline__ void pace(unsigned t0, int ns) { for (int i = 0; i < (1 << 16) && (int)(gtime() - t0) < ns; i++) {} }
__device__ __forceinline__ uint4 ld_poll(const void* p) {
    unsigned long long a, b;
    asm volatile("ld.relaxed.gpu.global.v2.b64 {%0,%1}, [%2];" : "=l"(a), "=l"(b) : "l"(p) : "memory");
    return make_uint4((uint32_t)a, (uint32_t)(a >> 32), (uint32_t)b, (uint32_t)(b >> 32));
}
__device__ __forceinline__ void st_pkt(const void* p, uint32_t v, uint32_t tag, uint32_t on) {
    asm volatile("{\n.reg .pred p;\n.reg .b64 d;\nsetp.ne.u32 p, %3, 0;\nmov.b64 d, {%1,%2};\n@p st.relaxed.gpu.global.b64 [%0], d;\n}" :: "l"(p), "r"(v), "r"(tag), "r"(on) : "memory");
}
__device__ __forceinline__ uint32_t pack_bf16(float lo, float hi) {
    uint32_t r; asm("cvt.rn.bf16x2.f32 %0, %1, %2;" : "=r"(r) : "f"(hi), "f"(lo)); return r;
}
__device__ __forceinline__ float bf_lo(uint32_t v) { return __uint_as_float(v << 16); }
__device__ __forceinline__ float bf_hi(uint32_t v) { return __uint_as_float(v & 0xffff0000u); }
__device__ __forceinline__ float ex2(float x) { float r; asm("ex2.approx.ftz.f32 %0, %1;" : "=f"(r) : "f"(x)); return r; }
__device__ __forceinline__ float warp_max(float v) {
    int i = __float_as_int(v);
    i ^= (i >> 31) & 0x7fffffff;
    i = __reduce_max_sync(0xffffffffu, i);
    i ^= (i >> 31) & 0x7fffffff;
    return __int_as_float(i);
}
__device__ __forceinline__ uint32_t ar_off(int k, int ln) {
    return (ln >> 1) * 1024 + (ln & 1) * 256 + (k & 1) * 128 + (k >> 1) * 512;
}

#define MMA4(A, i0, i1, i2, i3, b, d) \
    mma16(a0, A[i0], A[i0 + 1], A[i0 + 2], A[i0 + 3], b.x, b.y); \
    mma16(a1, A[i1], A[i1 + 1], A[i1 + 2], A[i1 + 3], b.z, b.w); \
    mma16(a2, A[i2], A[i2 + 1], A[i2 + 2], A[i2 + 3], d.x, d.y); \
    mma16(a3, A[i3], A[i3 + 1], A[i3 + 2], A[i3 + 3], d.z, d.w);
#define ZACC float a0[4] = {0.f, 0.f, 0.f, 0.f}, a1[4] = {0.f, 0.f, 0.f, 0.f}, a2[4] = {0.f, 0.f, 0.f, 0.f}, a3[4] = {0.f, 0.f, 0.f, 0.f}
#define PICK4 (fsel(t2, fsel(t1, a2[2], a2[0]), fsel(t1, a0[2], a0[0])) + fsel(t2, fsel(t1, a3[2], a3[0]), fsel(t1, a1[2], a1[0])))

__global__ void __cluster_dims__(2, 1, 1) __launch_bounds__(kNTHR, 1)
fused_kernel(const __nv_bfloat16* __restrict__ kc, const __nv_bfloat16* __restrict__ x0, __nv_bfloat16* __restrict__ out,
             const __grid_constant__ Sched sc, const __grid_constant__ CUtensorMap tm_wq, const __grid_constant__ CUtensorMap tm_v,
             const __grid_constant__ CUtensorMap tm_wo, const __grid_constant__ CUtensorMap tm_w1,
             const __grid_constant__ CUtensorMap tm_w3, const __grid_constant__ CUtensorMap tm_w2) {
    extern __shared__ uint8_t smem_raw[];
    const uint32_t sb = (smem_u32(smem_raw) + 1023u) & ~1023u;
    const uint32_t mb = sb + OFF_MB;
    const int tid = threadIdx.x;
    const int c = blockIdx.x;
    asm volatile("{\n.reg .pred p;\nsetp.eq.u32 p, %0, 352;\n"
                 "@p mbarrier.init.shared::cta.b64 [%1], 1;\n"
                 "@p fence.mbarrier_init.release.cluster;\n"
                 "@p mbarrier.arrive.expect_tx.shared::cta.b64 _, [%1], 65536;\n"
                 "@p cp.async.bulk.shared::cluster.global.mbarrier::complete_tx::bytes [%2], [%3], 65536, [%1];\n}"
                 :: "r"(tid), "r"(mb + MB_K * 8), "r"(sb + OFF_WO),
                    "l"((const char*)kc + ((size_t)(c >> 2) << 20) + (size_t)((kSK - kW) * kDH * 2 + (c & 3) * 65536)) : "memory");
    const unsigned t0 = gtime();
    const int warp = __shfl_sync(0xffffffffu, tid >> 5, 0), lane = tid & 31;
    const int h = c >> 2, j = c & 3, r = c & 1, p = c >> 1;
    const int g = lane >> 2, t = lane & 3;
    const bool ffn = p < kNFFN;
    char* const ar = (char*)(((uintptr_t)g_ar_raw + 32767) & ~(uintptr_t)32767);
    uint32_t rsb;
    asm("mapa.shared::cluster.u32 %0, %1, %2;" : "=r"(rsb) : "r"(sb), "r"(r ^ 1));

    if (warp >= 8) {
        asm volatile("setmaxnreg.dec.sync.aligned.u32 40;");
        const int cw = warp - 8;
        if (cw == 3) {
            if (lane >= 1 && lane < MB_COUNT) {
                const bool ex = lane >= MB_EX0 && lane < MB_MC0, fr = lane == MB_KFREE || lane == MB_VFREE;
                mbar_init(mb + lane * 8, fr ? 8 : ex ? 9 : 1);
                if (!fr && lane < MB_AL0) mbar_expect(mb + lane * 8, lane == MB_WQ ? 65536 : lane < MB_EX0 ? 16384 : lane < MB_EX0 + 2 ? 1024 : ex ? 512 : 16);
            }
            asm volatile("fence.mbarrier_init.release.cluster;" ::: "memory");
            __syncwarp();
        } else if (cw == 2 && lane < 6) {
            const CUtensorMap* tm = lane == 0 ? &tm_wq : lane == 1 ? &tm_v : lane == 2 ? &tm_wo : lane == 3 ? &tm_w1 : lane == 4 ? &tm_w3 : &tm_w2;
            asm volatile("prefetch.tensormap [%0];" :: "l"((uint64_t)tm) : "memory");
        }
        __syncwarp();
        asm volatile("barrier.cluster.arrive.relaxed.aligned;" ::: "memory");
        uint32_t xp = *(const uint32_t*)(x0 + r * 256 + cw * 64 + lane * 2);
        uint32_t xq = *(const uint32_t*)(x0 + (r ^ 1) * 256 + cw * 64 + lane * 2);
        sts32(sb + OFF_ONE + cw * 128 + lane * 4, 0x3F803F80u);
        sts32(sb + OFF_ZP + cw * 128 + lane * 4, 0u);
        if (lane < 4) sts32(sb + OFF_DL + lane * 4, sc.dar[lane]);
        __syncwarp();
        const uint32_t xs_a = __shfl_sync(0xffffffffu, sb + OFF_XS + cw * 128 + ((lane >> 4) & 1) * 64 + (lane & 3) * 16 + ((lane >> 3) & 1) * 8 + ((lane >> 2) & 1) * 4, lane);
        const uint32_t xf_a = __shfl_sync(0xffffffffu, sb + OFF_XF + cw * 128 + lane * 4, lane);
        const uint32_t ar_o = __shfl_sync(0xffffffffu, ar_off(0, r * 16 + cw * 4 + (lane >> 3)) + (lane & 7) * 16, lane);
        const uint32_t dst01 = __shfl_sync(0xffffffffu, (lane & 1) ? rsb : sb, lane);
        const uint32_t mode01 = lane < 2 ? 2u : 0u;

        auto xstage = [&](int st) -> bool {
            const uint32_t tg = __float_as_uint((st & 1) ? 64.f : (float)kNFFN);
            const bool act = ffn || !(st & 1);
            const char* a = ar + (ar_o + ((st - 1) & 1) * 128 + ((st - 1) >> 1) * 512);
            const char* a2 = (const char*)((uintptr_t)a ^ 8192);
            uint4 u = make_uint4(0, tg, 0, tg);
            if (st > 0) {
                const int dar = lds32(sb + OFF_DL + st * 4);
                if (ffn || (st & 1)) bar_sync(B_RED, 384);
                if (!ffn) {
                    if (st == 3) return false;
                    spin(st == 1 ? 1500 : 400);
                }
                spin(dar);
                if (st >= 2 && cw == 0) TS(60 + st);
                uint4 v;
#pragma unroll 1
                for (int it = 0; it < (1 << 18); it++) {
                    v = ld_poll(a);
                    u = ld_poll(a2);
                    if (__all_sync(0xffffffffu, v.y == tg && v.w == tg)) break;
                }
                const uint32_t d = pack_bf16(__uint_as_float(v.x), __uint_as_float(v.z));
                xp = pack_bf16(bf_lo(xp) + bf_lo(d), bf_hi(xp) + bf_hi(d));
            }
            if (act) {
                sts32(xs_a, xp);
                sts32(xf_a, xp);
                bar_arrive(B_X, 384);
            }
            if (cw == 0) TS(1 + st * 6);
            if (st >= 2) TS(46 + st * 4 + cw);
#pragma unroll 1
            for (int it = 0; it < (1 << 18); it++) {
                if (__all_sync(0xffffffffu, u.y == tg && u.w == tg)) break;
                u = ld_poll(a2);
            }
            const uint32_t d = pack_bf16(__uint_as_float(u.x), __uint_as_float(u.z));
            xq = pack_bf16(bf_lo(xq) + bf_lo(d), bf_hi(xq) + bf_hi(d));
            if (!act) return false;
            const float xa = bf_lo(xp), xb = bf_hi(xp), xc = bf_lo(xq), xd = bf_hi(xq);
            float s1 = (xa + xb) + (xc + xd), s2 = fmaf(xa, xa, xb * xb) + fmaf(xc, xc, xd * xd);
#pragma unroll
            for (int o = 16; o > 0; o >>= 1) { s1 += __shfl_xor_sync(0xffffffffu, s1, o); s2 += __shfl_xor_sync(0xffffffffu, s2, o); }
            if (lane == 0) sts64f(sb + OFF_RS + cw * 8, s1, s2);
            if (cw == 0) bar_sync(B_ST, 128); else bar_arrive(B_ST, 128);
            return true;
        };
        auto phi_stage = [&](const char* sp, uint32_t tag, int layer) {
            uint4 e0, e1, e2, e3;
#pragma unroll 1
            for (int it = 0; it < (1 << 18); it++) {
                e0 = ld_poll(sp); e1 = ld_poll(sp + 32); e2 = ld_poll(sp + 64); e3 = ld_poll(sp + 96);
                if (e0.y == tag && e0.w == tag && e1.y == tag && e1.w == tag && e2.y == tag && e2.w == tag && e3.y == tag && e3.w == tag) break;
            }
            const float Ma = fmaxf(__uint_as_float(e0.x), __uint_as_float(e1.x)), Mb = fmaxf(__uint_as_float(e2.x), __uint_as_float(e3.x));
            const float Mh = fmaxf(Ma, Mb);
            const float Lh = fmaf(ex2(__uint_as_float(e0.x) - Mh), __uint_as_float(e0.z), ex2(__uint_as_float(e1.x) - Mh) * __uint_as_float(e1.z)) +
                             fmaf(ex2(__uint_as_float(e2.x) - Mh), __uint_as_float(e2.z), ex2(__uint_as_float(e3.x) - Mh) * __uint_as_float(e3.z));
            if (lane == 0) sts64(sb + OFF_PHI, __float_as_uint(__fdividef(ex2(((j & 2) ? Mb : Ma) - Mh), Lh)), layer + 1);
        };

        if (cw == 0) {
            asm volatile("barrier.cluster.wait.acquire.aligned;" ::: "memory");
            const uint32_t l16 = __shfl_sync(0xffffffffu, sb + lane * 16, lane);
            const uint32_t qs_a = __shfl_sync(0xffffffffu, sb + OFF_QS + g * 32 + t * 4, lane);
            const uint32_t os_a = __shfl_sync(0xffffffffu, sb + OFF_OS + (g >> 1) * 64 + t * 16 + (g & 1) * 8, lane);
            const uint32_t hs_a = __shfl_sync(0xffffffffu, sb + OFF_HS + ((lane & 7) >> 1) * 16 + (lane >> 4) * 8 + ((lane >> 3) & 1) * 4 + (lane & 1) * 2, lane);
            float cs[4] = {0.f, 0.f, 0.f, 0.f}, c1 = 0.f, c3 = 0.f;
#pragma unroll 1
            for (int st = 0; st < 4; st++) {
                if (!xstage(st)) continue;
                const float4 r0 = lds128f(sb + OFF_RS), r1 = lds128f(sb + OFF_RS + 16);
                const float mean = ((r0.x + r0.z) + (r1.x + r1.z)) * (1.f / kD);
                const float ex2m = fmaf((r0.y + r0.w) + (r1.y + r1.w), 1.f / kD, 1e-5f);
                const float rstd = rsq(fmaxf(fmaf(-mean, mean, ex2m), 1e-5f));
                const float nmr = -mean * rstd;
                if (st >= 2) TS(50 + st);
                if (!(st & 1)) {
                    mbar_wait(mb + (MB_EX0 + st) * 8);
                    TS(2 + st * 6);
                    const float4 a = lds128f(l16 + OFF_QP), b = lds128f(l16 + OFF_QP + 512);
                    if (st == 0) {
                        const float4 u = lds128f(l16 + OFF_QP + 1024), w = lds128f(l16 + OFF_QP + 1536);
                        cs[0] = u.x + w.x; cs[1] = u.y + w.y; cs[2] = u.z + w.z; cs[3] = u.w + w.w;
                    }
                    const float q0 = fmaf(rstd, a.x + b.x, nmr * cs[0]), q8 = fmaf(rstd, a.y + b.y, nmr * cs[1]);
                    const float q1 = fmaf(rstd, a.z + b.z, nmr * cs[2]), q9 = fmaf(rstd, a.w + b.w, nmr * cs[3]);
                    sts32(qs_a, pack_bf16(q0, q1));
                    sts32(qs_a + 16, pack_bf16(q8, q9));
                    bar_arrive(B_Q, 288);
                    if (st == 0) {
                        const unsigned want = lds32(sb + OFF_EP) + 1;
#pragma unroll 1
                        for (int it = 0; it < (1 << 18); it++) {
                            unsigned fl;
                            asm volatile("ld.acquire.gpu.global.u32 %0, [%1];" : "=r"(fl) : "l"(g_flag_line + (lane & 15)) : "memory");
                            if (__all_sync(0xffffffffu, fl == want)) break;
                        }
                    }
                    mbar_wait(mb + (MB_MC0 + (st >> 1)) * 8);
                    const float4 mc = lds128f(sb + OFF_MC + (st >> 1) * 16);
                    const float Mp = fmaxf(mc.x, mc.z);
                    const float w0 = ex2(mc.x - Mp), w1 = ex2(mc.z - Mp);
                    mbar_wait(mb + (MB_OX0 + (st >> 1)) * 8);
                    TS(4 + st * 6);
                    const float4 d = lds128f(l16 + OFF_OP), e = lds128f(l16 + OFF_OP + 512);
                    sts64(os_a, pack_bf16(fmaf(w0, d.x, w1 * e.x), fmaf(w0, d.z, w1 * e.z)), pack_bf16(fmaf(w0, d.y, w1 * e.y), fmaf(w0, d.w, w1 * e.w)));
                    bar_arrive(B_O, 288);
                    TS(5 + st * 6);
                } else {
                    mbar_wait(mb + (MB_EX0 + st) * 8);
                    TS(2 + st * 6);
                    const float4 a = lds128f(l16 + OFF_HP), b = lds128f(l16 + OFF_HP + 512);
                    if (st == 1) {
                        const float4 u = lds128f(l16 + OFF_HP + 1024), w = lds128f(l16 + OFF_HP + 1536);
                        c1 = (u.x + u.z) + (w.x + w.z); c3 = (u.y + u.w) + (w.y + w.w);
                    }
                    const float gate = fmaf(rstd, (a.x + a.z) + (b.x + b.z), nmr * c1), up = fmaf(rstd, (a.y + a.w) + (b.y + b.w), nmr * c3);
                    const float hv = __fdividef(gate * up, 1.f + ex2(-1.4426950408889634f * gate));
                    sts16(hs_a, pack_bf16(hv, 0.f));
                    bar_arrive(B_H, 288);
                    TS(3 + st * 6);
                }
            }
        } else if (cw == 1) {
            unsigned epoch;
            asm volatile("ld.relaxed.gpu.global.u32 %0, [%1];" : "=r"(epoch) : "l"(g_epoch_line) : "memory");
            const char* const my_st = ar + 16384 + c * 32 + t * 8 + (g & 1) * 4096;
            st_pkt(my_st, 0, 0, lane < 8);
            if (lane == 0) { sts64(sb + OFF_PHI, 0, 0); sts32(sb + OFF_EP, epoch); }
            asm volatile("barrier.cluster.wait.acquire.aligned;" ::: "memory");
#pragma unroll 1
            for (int st = 0; st < 4; st++) {
                if (!xstage(st) || (st & 1)) continue;
                const uint32_t tag = epoch * 2 + (st >> 1) + 1;
                bar_sync(B_S, 320);
                const uint4 pv = lds128(sb + OFF_PS + lane * 16);
                const float4 m0 = lds128f(sb + OFF_MS), m1 = lds128f(sb + OFF_MS + 16);
                const float mg = __uint_as_float(lds32(sb + OFF_MS + g * 4));
                const float M = fmaxf(fmaxf(fmaxf(m0.x, m0.y), fmaxf(m0.z, m0.w)), fmaxf(fmaxf(m1.x, m1.y), fmaxf(m1.z, m1.w)));
                const float al = ex2(mg - M);
                sts32(sb + OFF_MS + 32 + g * 4, __float_as_uint(al));
                __syncwarp();
                if (lane == 0) mbar_arrive(mb + (MB_AL0 + (st >> 1)) * 8);
                const float lp = (((bf_lo(pv.x) + bf_hi(pv.x)) + (bf_lo(pv.y) + bf_hi(pv.y))) + ((bf_lo(pv.z) + bf_hi(pv.z)) + (bf_lo(pv.w) + bf_hi(pv.w)))) * (al * 8388608.f);
                const float L = __uint2float_rn(__reduce_add_sync(0xffffffffu, __float2uint_rn(lp))) * (1.f / 8388608.f);
                st_pkt(my_st, __float_as_uint((lane & 1) ? L : M), tag, lane < 8);
                send_pair(dst01 + OFF_MC + (st >> 1) * 16 + r * 8, dst01 + OFF_MB + (MB_MC0 + (st >> 1)) * 8, M, M, mode01);
                TS(3 + st * 6);
                spin(lds32(sb + OFF_DL));
                phi_stage(ar + 16384 + h * 128, tag, st >> 1);
                TS(6 + st * 6);
            }
        } else if (cw == 2) {
            unsigned epoch;
            asm volatile("ld.relaxed.gpu.global.u32 %0, [%1];" : "=r"(epoch) : "l"(g_epoch_line) : "memory");
            if (c < 16) {
                asm volatile("st.relaxed.gpu.global.v4.u32 [%0], {%1,%1,%1,%1};" :: "l"(ar + c * 1024 + lane * 16), "r"(0) : "memory");
                asm volatile("st.relaxed.gpu.global.v4.u32 [%0], {%1,%1,%1,%1};" :: "l"(ar + c * 1024 + 512 + lane * 16), "r"(0) : "memory");
                __threadfence();
                __syncwarp();
                if (lane == 0) asm volatile("st.relaxed.gpu.global.u32 [%0], %1;" :: "l"(g_flag_line + c), "r"(epoch + 1) : "memory");
            }
            asm volatile("barrier.cluster.wait.acquire.aligned;" ::: "memory");
#pragma unroll 1
            for (int st = 0; st < 4; st++) {
                if (!xstage(st) || (st & 1)) continue;
                bar_sync(B_S, 320);
                spin(lds32(sb + OFF_DL) + 200);
                phi_stage(ar + 16384 + 4096 + h * 128, epoch * 2 + (st >> 1) + 1, st >> 1);
                if (st == 2) TS(23);
            }
        } else {
            asm volatile("barrier.cluster.wait.acquire.aligned;" ::: "memory");
            if (lane == 0) {
#pragma unroll 1
                for (int q = 0; q < 4; q++) {
                    pace(t0, sc.tq[q]);
                    tma2d(sb + OFF_WQ + q * 8192, &tm_wq, h * 128, r * 256 + q * 64, mb + MB_WQ * 8);
                    tma2d(sb + OFF_WQ + 32768 + q * 8192, &tm_wq, h * 128 + 64, r * 256 + q * 64, mb + MB_WQ * 8);
                }
            }
            __syncwarp();
#pragma unroll 1
            for (int st = 0; st < 4; st++) {
                xstage(st);
                if (st == 0 && lane == 0) {
                    const int vrow = h * kSK + (kSK - kW) + j * 256;
#pragma unroll 1
                    for (int i = 0; i < 11; i++) {
                        const int id = sc.id[i], q = id & 3;
                        if (id >= 8 && !ffn) continue;
                        pace(t0, sc.t[i]);
                        const uint32_t bar = mb + (MB_V0 + id) * 8;
                        if (id < 4) {
                            tma2d(sb + OFF_V + q * 16384, &tm_v, 0, vrow + q * 64, bar);
                            tma2d(sb + OFF_V + q * 16384 + 8192, &tm_v, 64, vrow + q * 64, bar);
                        } else if (id < 8) {
                            mbar_wait(mb + MB_KFREE * 8);
#pragma unroll 1
                            for (int b = 0; b < 4; b++) tma2d(sb + OFF_WO + b * 16384 + q * 4096, &tm_wo, r * 256 + b * 64, h * 128 + q * 32, bar);
                        } else {
                            mbar_wait(mb + MB_VFREE * 8);
                            if (id < 10) {
                                tma2d(sb + OFF_W1 + q * 8192, &tm_w1, p * 32, r * 256 + q * 128, bar);
                                tma2d(sb + OFF_W3 + q * 8192, &tm_w3, p * 32, r * 256 + q * 128, bar);
                            } else {
#pragma unroll 1
                                for (int b = 0; b < 4; b++) tma2d(sb + OFF_W2 + b * 4096, &tm_w2, r * 256 + b * 64, p * 32, bar);
                            }
                        }
                    }
                }
                __syncwarp();
            }
        }
    } else {
        asm volatile("setmaxnreg.inc.sync.aligned.u32 232;");
        asm volatile("barrier.cluster.arrive.relaxed.aligned;" ::: "memory");
        const int w = warp;
        const bool t1 = t & 1, t2 = t & 2, l0 = lane == 0;
        uint32_t KR[64], VR[64], S[64];
        {
            const int mt = w & 3, kh = w >> 2, ln = w + 8 * (t >> 1), cc = g + 8 * (t & 1);
            const uint32_t snd = ((t & 1) ? rsb : sb) + r * 512 + (t >> 1) * 1024;
            const uint64_t arc = (uint64_t)(ar + ar_off(0, r * 16 + ln) + cc * 8), op = (uint64_t)(out + r * 256 + ln * 16 + cc);
            const uint32_t xb = sb + ((g & 1) ? OFF_ONE : OFF_XS) + t * 16;
            sts128(sb + OFF_TAB + tid * 16, xb, snd + OFF_QP + w * 64 + g * 8, sb + OFF_PS + (w * 4 + (g >> 1)) * 16 + t * 4 + (g & 1) * 2,
                   sb + ((g & 1) ? OFF_PS : OFF_ZP) + 64 + t * 16);
            sts128(sb + OFF_TAB + 4096 + tid * 16, (uint32_t)arc, (uint32_t)(arc >> 32), xb + kh * 256, snd + OFF_HP + (mt * 8 + g) * 16 + kh * 8);
            sts128(sb + OFF_TAB + 8192 + tid * 16, (uint32_t)op, (uint32_t)(op >> 32), sb + OFF_XF + (ln * 16 + cc) * 2,
                   sb + OFF_W1 + ((lane >> 3) & 1) * 16384 + (kh * 128 + (lane >> 4) * 8 + (lane & 7)) * 64 + ((mt ^ ((lane >> 1) & 3)) << 4));
        }
        const uint32_t tab = __shfl_sync(0xffffffffu, sb + OFF_TAB + tid * 16, lane);
        const uint32_t t16 = __shfl_sync(0xffffffffu, sb + t * 16, lane);
        const uint32_t lm = __shfl_sync(0xffffffffu, sb + ((lane >> 4) * 8 + (lane & 7)) * 128 + ((((w & 3) * 2 + ((lane >> 3) & 1)) ^ (lane & 7)) << 4), lane);
        const uint32_t wh = w >> 2;
        asm volatile("barrier.cluster.wait.acquire.aligned;" ::: "memory");
        mbar_wait(mb + MB_K * 8);
        if (w == 0) TS(24);
        {
            const uint32_t kp = sb + OFF_WO + (w * 32 + g) * 256 + t * 16;
#pragma unroll
            for (int rr = 0; rr < 4; rr++)
#pragma unroll
                for (int i = 0; i < 4; i++) {
                    const uint4 v = lds128(kp + rr * 2048 + i * 64);
                    uint32_t* d = &KR[(rr >> 1) * 32 + i * 8 + (rr & 1)];
                    d[0] = v.x; d[2] = v.y; d[4] = v.z; d[6] = v.w;
                }
        }
        __syncwarp();
        if (l0) mbar_arrive(mb + MB_KFREE * 8);
#pragma unroll
        for (int i = 0; i < 64; i++) VR[i] = 0;

#pragma unroll 1
        for (int layer = 0; layer < 2; layer++) {
            const uint32_t smode = (!t2 || layer == 0) ? (t1 ? 2u : 1u) : 0u;
            const uint32_t exb = OFF_MB + (MB_EX0 + layer * 2) * 8;
            const uint32_t lm_wo = lm + OFF_WO + wh * 16384;
            mbar_wait(mb + MB_WQ * 8);
            if (w == 0 && layer == 0) TS(25);
#pragma unroll
            for (int s = 0; s < 16; s++) ldsm4t(&S[s * 4], lm + OFF_WQ + wh * 32768 + s * 2048);
            const uint4 T0 = lds128(tab);
            {
                bar_sync(B_X, 384);
                ZACC;
#pragma unroll
                for (int i = 0; i < 4; i++) {
                    const uint4 b = lds128(T0.x + i * 128), d = lds128(T0.x + i * 128 + 64);
                    MMA4(S, i * 16, i * 16 + 4, i * 16 + 8, i * 16 + 12, b, d);
                }
                const float v0 = (fsel(t2, a0[1], a0[0]) + fsel(t2, a1[1], a1[0])) + (fsel(t2, a2[1], a2[0]) + fsel(t2, a3[1], a3[0]));
                const float v1 = (fsel(t2, a0[3], a0[2]) + fsel(t2, a1[3], a1[2])) + (fsel(t2, a2[3], a2[2]) + fsel(t2, a3[3], a3[2]));
                send_pair(T0.y, rsb + exb, v0, v1, smode);
                __syncwarp();
                if (l0) mbar_arrive(sb + exb);
                TW(2);
            }
#pragma unroll
            for (int s = 0; s < 4; s++) ldsm4t(&S[s * 4], lm_wo + s * 2048);
            {
                bar_sync(B_Q, 288);
                uint4 b[4];
#pragma unroll
                for (int i = 0; i < 3; i++) b[i] = lds128(t16 + OFF_QS + i * 64);
#pragma unroll
                for (int s = 4; s < 8; s++) ldsm4t(&S[s * 4], lm_wo + s * 2048);
                __syncwarp();
                b[3] = lds128(t16 + OFF_QS + 192);
                ZACC;
#pragma unroll
                for (int i = 0; i < 4; i++) { MMA4(KR, i * 8, i * 8 + 4, 32 + i * 8, 32 + i * 8 + 4, b[i], b[i]); }
                const float sv = PICK4 * (0.08838834764831845f * 1.4426950408889634f);
                TWD(3, sv);
                const float m = warp_max(sv);
                sts16(T0.z, pack_bf16(ex2(sv - m), 0.f));
                if (l0) sts32(sb + OFF_MS + w * 4, __float_as_uint(m));
            }
            bar_sync(B_S, 320);
            if (layer == 0) {
#pragma unroll
                for (int q = 0; q < 4; q++) {
                    mbar_wait(mb + (MB_V0 + q) * 8);
#pragma unroll
                    for (int s = 0; s < 4; s++) ldsm4t(&VR[(q * 4 + s) * 4], lm + OFF_V + q * 16384 + wh * 8192 + s * 2048);
                    if (q == 2) {
                        __syncwarp();
                        if (l0) mbar_arrive(mb + MB_VFREE * 8);
                    }
                }
                if (w == 0) TS(26);
            }
            {
                const uint32_t pe = T0.x + (OFF_PS - OFF_XS), po = T0.w;
                uint4 b[8];
#pragma unroll
                for (int i = 0; i < 4; i++) b[i] = lds128(pe + i * 128);
#pragma unroll
                for (int s = 0; s < 4; s++) ldsm4t(&S[32 + s * 4], lm_wo + 32768 + s * 2048);
                __syncwarp();
#pragma unroll
                for (int i = 0; i < 4; i++) b[4 + i] = lds128(po + i * 128);
                ZACC;
                float4 wa, wb;
#pragma unroll
                for (int hf = 0; hf < 2; hf++) {
                    if (hf == 1) {
                        mbar_wait(mb + (MB_AL0 + layer) * 8);
                        wa = lds128f(sb + OFF_MS + 32); wb = lds128f(sb + OFF_MS + 48);
                    }
                    mma16(a0, VR[hf * 8 + 0], VR[hf * 8 + 1], VR[hf * 8 + 2], VR[hf * 8 + 3], b[hf * 4 + 0].x, b[hf * 4 + 0].y);
                    mma16(a1, VR[hf * 8 + 16], VR[hf * 8 + 17], VR[hf * 8 + 18], VR[hf * 8 + 19], b[hf * 4 + 1].x, b[hf * 4 + 1].y);
                    mma16(a2, VR[hf * 8 + 32], VR[hf * 8 + 33], VR[hf * 8 + 34], VR[hf * 8 + 35], b[hf * 4 + 2].x, b[hf * 4 + 2].y);
                    mma16(a3, VR[hf * 8 + 48], VR[hf * 8 + 49], VR[hf * 8 + 50], VR[hf * 8 + 51], b[hf * 4 + 3].x, b[hf * 4 + 3].y);
                    mma16(a0, VR[hf * 8 + 4], VR[hf * 8 + 5], VR[hf * 8 + 6], VR[hf * 8 + 7], b[hf * 4 + 0].z, b[hf * 4 + 0].w);
                    mma16(a1, VR[hf * 8 + 20], VR[hf * 8 + 21], VR[hf * 8 + 22], VR[hf * 8 + 23], b[hf * 4 + 1].z, b[hf * 4 + 1].w);
                    mma16(a2, VR[hf * 8 + 36], VR[hf * 8 + 37], VR[hf * 8 + 38], VR[hf * 8 + 39], b[hf * 4 + 2].z, b[hf * 4 + 2].w);
                    mma16(a3, VR[hf * 8 + 52], VR[hf * 8 + 53], VR[hf * 8 + 54], VR[hf * 8 + 55], b[hf * 4 + 3].z, b[hf * 4 + 3].w);
                }
                const float ol = (fmaf(wa.x, a0[0], wa.y * a0[1]) + fmaf(wa.z, a1[0], wa.w * a1[1])) + (fmaf(wb.x, a2[0], wb.y * a2[1]) + fmaf(wb.z, a3[0], wb.w * a3[1]));
                const float oh = (fmaf(wa.x, a0[2], wa.y * a0[3]) + fmaf(wa.z, a1[2], wa.w * a1[3])) + (fmaf(wb.x, a2[2], wb.y * a2[3]) + fmaf(wb.z, a3[2], wb.w * a3[3]));
                TWD(6, ol);
                send_pair(T0.y + (OFF_OP - OFF_QP), rsb + OFF_MB + (MB_OX0 + layer) * 8, ol, oh, t2 ? 0u : (t1 ? 2u : 1u));
                __syncwarp();
                if (l0) mbar_arrive(mb + (MB_OX0 + layer) * 8);
                TW(7);
            }
            if (layer == 0) {
#pragma unroll
                for (int q = 0; q < 4; q++) {
                    mbar_wait(mb + (MB_WO0 + q) * 8);
                    ldsm4t(&S[q * 8], lm_wo + q * 4096); ldsm4t(&S[q * 8 + 4], lm_wo + q * 4096 + 2048);
                    if (q < 2) { ldsm4t(&S[32 + q * 8], lm_wo + 32768 + q * 4096); ldsm4t(&S[32 + q * 8 + 4], lm_wo + 32768 + q * 4096 + 2048); }
                }
                if (w == 0) TS(27);
            }
#pragma unroll
            for (int s = 4; s < 8; s++) ldsm4t(&S[32 + s * 4], lm_wo + 32768 + s * 2048);
            const uint4 T1 = lds128(tab + 4096);
            {
                bar_sync(B_O, 288);
                uint4 b[4];
#pragma unroll
                for (int i = 0; i < 4; i++) b[i] = lds128(t16 + OFF_OS + i * 64);
                float2 ph = lds64f(sb + OFF_PHI);
                ZACC;
#pragma unroll
                for (int i = 0; i < 4; i++) { MMA4(S, i * 8, i * 8 + 4, 32 + i * 8, 32 + i * 8 + 4, b[i], b[i]); }
#pragma unroll 1
                for (int it = 0; it < (1 << 22) && __float_as_uint(ph.y) != (uint32_t)layer + 1; it++) ph = lds64f(sb + OFF_PHI);
                const float v = PICK4 * ph.x;
                red_pair(mk64(T1.x, T1.y) + layer * 512, v, 1);
                bar_arrive(B_RED, 384);
                TW(11);
            }
            if (!ffn) continue;
            const uint32_t w2a = lm + OFF_W2 + wh * 4096;
            const uint4 T2 = lds128(tab + 8192);
            {
                mbar_wait(mb + (MB_W130 + wh) * 8);
                if (w == 4 && layer == 0) TS(28);
#pragma unroll
                for (int s = 0; s < 8; s++) ldsm4t(&S[s * 4], T2.w + s * 1024);
                ldsm4t(&S[32], w2a); ldsm4t(&S[36], w2a + 2048); ldsm4t(&S[40], w2a + 8192); ldsm4t(&S[44], w2a + 8192 + 2048);
                bar_sync(B_X, 384);
                ZACC;
#pragma unroll
                for (int i = 0; i < 2; i++) {
                    const uint4 b = lds128(T1.z + i * 128), d = lds128(T1.z + i * 128 + 64);
                    MMA4(S, i * 16, i * 16 + 4, i * 16 + 8, i * 16 + 12, b, d);
                }
                const float v0 = (fsel(t2, a0[1], a0[0]) + fsel(t2, a1[1], a1[0])) + (fsel(t2, a2[1], a2[0]) + fsel(t2, a3[1], a3[0]));
                const float v1 = (fsel(t2, a0[3], a0[2]) + fsel(t2, a1[3], a1[2])) + (fsel(t2, a2[3], a2[2]) + fsel(t2, a3[3], a3[2]));
                send_pair(T1.w, rsb + exb + 8, v0, v1, smode);
                __syncwarp();
                if (l0) mbar_arrive(sb + exb + 8);
                TW(14);
            }
            if (layer == 0) {
                mbar_wait(mb + MB_W2 * 8);
                if (w == 0) TS(29);
                ldsm4t(&S[32], w2a); ldsm4t(&S[36], w2a + 2048); ldsm4t(&S[40], w2a + 8192); ldsm4t(&S[44], w2a + 8192 + 2048);
            }
            {
                uint16_t xr; asm volatile("ld.shared.u16 %0, [%1];" : "=h"(xr) : "r"(T2.z) : "memory");
                const uint32_t epoch = lds32(sb + OFF_EP);
                bar_sync(B_H, 288);
                const uint4 b = lds128(t16 + OFF_HS);
                ZACC;
                MMA4(S, 32, 36, 40, 44, b, b);
                const float v = PICK4;
                TWD(16, v);
                if (layer == 0) {
                    red_pair(mk64(T1.x, T1.y) + 128, v, 1);
                    bar_arrive(B_RED, 384);
                } else {
                    float ov, oc;
                    asm volatile("atom.relaxed.gpu.global.add.v2.f32 {%0,%1}, [%2], {%3,%4};" : "=f"(ov), "=f"(oc) : "l"(mk64(T1.x, T1.y) + 640), "f"(v), "f"(1.f) : "memory");
                    if (oc == (float)(kNFFN - 1)) {
                        const float y = __uint_as_float((uint32_t)xr << 16) + bf_lo(pack_bf16(ov + v, 0.f));
                        asm volatile("st.global.u16 [%0], %1;" :: "l"(mk64(T2.x, T2.y)), "h"((uint16_t)pack_bf16(y, 0.f)) : "memory");
                        if (r == 0 && w == 0 && l0) asm volatile("st.relaxed.gpu.global.u32 [%0], %1;" :: "l"(g_epoch_line), "r"(epoch + 1) : "memory");
                    }
                }
            }
        }
    }
}

__device__ __forceinline__ float bfr(float v) { return __bfloat162float(__float2bfloat16(v)); }
__global__ void fb_ln(const __nv_bfloat16* x0, int first) {
    __shared__ float red[2][16];
    const int tid = threadIdx.x;
    float x = first ? __bfloat162float(x0[tid]) : g_fb[tid];
    g_fb[tid] = x;
    float s = x;
    for (int o = 16; o > 0; o >>= 1) s += __shfl_xor_sync(0xffffffffu, s, o);
    if ((tid & 31) == 0) red[0][tid >> 5] = s;
    __syncthreads();
    float m = 0.f;
    for (int i = 0; i < 16; i++) m += red[0][i];
    m *= 1.f / kD;
    float d = (x - m) * (x - m);
    for (int o = 16; o > 0; o >>= 1) d += __shfl_xor_sync(0xffffffffu, d, o);
    if ((tid & 31) == 0) red[1][tid >> 5] = d;
    __syncthreads();
    float v = 0.f;
    for (int i = 0; i < 16; i++) v += red[1][i];
    g_fb[512 + tid] = (x - m) * rsqrtf(v * (1.f / kD) + 1e-5f);
}
__global__ void fb_attn(const __nv_bfloat16* kc, const __nv_bfloat16* vc, const __nv_bfloat16* wq) {
    __shared__ float q[128], s[1024], red[32];
    const int h = blockIdx.x, tid = threadIdx.x;
    if (tid < 128) {
        float a = 0.f;
        for (int d = 0; d < kD; d++) a += g_fb[512 + d] * __bfloat162float(wq[(size_t)d * 4096 + h * 128 + tid]);
        q[tid] = bfr(a);
    }
    __syncthreads();
    const __nv_bfloat16* kr = kc + ((size_t)h * kSK + (kSK - kW) + tid) * kDH;
    float a = 0.f;
    for (int d = 0; d < kDH; d++) a += q[d] * __bfloat162float(kr[d]);
    a *= 0.08838834764831845f;
    float m = a;
    for (int o = 16; o > 0; o >>= 1) m = fmaxf(m, __shfl_xor_sync(0xffffffffu, m, o));
    if ((tid & 31) == 0) red[tid >> 5] = m;
    __syncthreads();
    for (int i = 0; i < 32; i++) m = fmaxf(m, red[i]);
    __syncthreads();
    const float e = expf(a - m);
    s[tid] = e;
    float l = e;
    for (int o = 16; o > 0; o >>= 1) l += __shfl_xor_sync(0xffffffffu, l, o);
    if ((tid & 31) == 0) red[tid >> 5] = l;
    __syncthreads();
    l = 0.f;
    for (int i = 0; i < 32; i++) l += red[i];
    if (tid < 128) {
        float o = 0.f;
        const __nv_bfloat16* vr = vc + ((size_t)h * kSK + (kSK - kW)) * kDH + tid;
        for (int k = 0; k < kW; k++) o += s[k] * __bfloat162float(vr[(size_t)k * kDH]);
        g_fb[1024 + h * 128 + tid] = bfr(o / l);
    }
}
__global__ void fb_up(const __nv_bfloat16* w1, const __nv_bfloat16* w3) {
    const int f = blockIdx.x * blockDim.x + threadIdx.x;
    if (f >= kF) return;
    float a = 0.f, b = 0.f;
    for (int d = 0; d < kD; d++) { a += g_fb[512 + d] * __bfloat162float(w1[(size_t)d * kF + f]); b += g_fb[512 + d] * __bfloat162float(w3[(size_t)d * kF + f]); }
    g_fb[5120 + f] = bfr(a / (1.f + expf(-a)) * b);
}
__global__ void fb_down(const __nv_bfloat16* w, int src, int n, __nv_bfloat16* out) {
    const int col = blockIdx.x * blockDim.x + threadIdx.x;
    float a = 0.f;
    for (int k = 0; k < n; k++) a += g_fb[src + k] * __bfloat162float(w[(size_t)k * kD + col]);
    const float y = bfr(g_fb[col] + bfr(a));
    g_fb[col] = y;
    if (out) out[col] = __float2bfloat16(y);
}

typedef CUresult (*EncodeFn)(CUtensorMap*, CUtensorMapDataType, cuuint32_t, void*, const cuuint64_t*, const cuuint64_t*,
                             const cuuint32_t*, const cuuint32_t*, CUtensorMapInterleave, CUtensorMapSwizzle,
                             CUtensorMapL2promotion, CUtensorMapFloatOOBfill);

bool make_map(EncodeFn fn, CUtensorMap* m, const void* base, uint64_t cols, uint64_t rows, uint32_t bc, uint32_t br, CUtensorMapSwizzle swz) {
    cuuint64_t dims[2] = {cols, rows};
    cuuint64_t strides[1] = {cols * 2};
    cuuint32_t box[2] = {bc, br};
    cuuint32_t es[2] = {1, 1};
    return fn(m, CU_TENSOR_MAP_DATA_TYPE_BFLOAT16, 2, const_cast<void*>(base), dims, strides, box, es, CU_TENSOR_MAP_INTERLEAVE_NONE,
              swz, CU_TENSOR_MAP_L2_PROMOTION_NONE, CU_TENSOR_MAP_FLOAT_OOB_FILL_NONE) == CUDA_SUCCESS;
}

Sched g_sched = {{2120, 2460, 2800, 3140},
                 {0, 1, 2, 3, 4, 5, 6, 7, 8, 9, 10},
                 {3480, 4160, 4840, 5520, 6200, 6540, 6880, 7220, 7860, 8320, 8780},
                 {150, 250, 250, 250}};

}

extern "C" void kernel_launch(void* const* d_in, const int* in_sizes, int n_in, void* d_out, int out_size) {
    (void)in_sizes; (void)n_in; (void)out_size;
    const __nv_bfloat16* x0 = (const __nv_bfloat16*)d_in[0];
    const __nv_bfloat16* kc = (const __nv_bfloat16*)d_in[1];
    const __nv_bfloat16* vc = (const __nv_bfloat16*)d_in[2];
    const __nv_bfloat16* wq = (const __nv_bfloat16*)d_in[3];
    const __nv_bfloat16* wo = (const __nv_bfloat16*)d_in[4];
    const __nv_bfloat16* w1 = (const __nv_bfloat16*)d_in[6];
    const __nv_bfloat16* w3 = (const __nv_bfloat16*)d_in[7];
    const __nv_bfloat16* w2 = (const __nv_bfloat16*)d_in[8];
    __nv_bfloat16* out = (__nv_bfloat16*)d_out;
    cudaStream_t s = cudaStreamPerThread;

    static int state = 0;
    static EncodeFn enc = nullptr;
    if (state == 0) {
        state = 2;
        void* fn = nullptr;
        cudaDriverEntryPointQueryResult qr;
        if (cudaGetDriverEntryPoint("cuTensorMapEncodeTiled", &fn, cudaEnableDefault, &qr) == cudaSuccess && fn &&
            cudaFuncSetAttribute(fused_kernel, cudaFuncAttributeMaxDynamicSharedMemorySize, SMEM_BYTES) == cudaSuccess) {
            enc = (EncodeFn)fn;
            cudaLaunchConfig_t cfg = {};
            cfg.gridDim = dim3(kNCTA); cfg.blockDim = dim3(kNTHR); cfg.dynamicSmemBytes = SMEM_BYTES;
            cudaLaunchAttribute at[1];
            at[0].id = cudaLaunchAttributeClusterDimension;
            at[0].val.clusterDim.x = 2; at[0].val.clusterDim.y = 1; at[0].val.clusterDim.z = 1;
            cfg.attrs = at; cfg.numAttrs = 1;
            int ncl = 0;
            if (cudaOccupancyMaxActiveClusters(&ncl, fused_kernel, &cfg) == cudaSuccess && ncl >= kNCTA / 2) state = 1;
        }
        (void)cudaGetLastError();
    }
    if (state == 1) {
        CUtensorMap m_wq, m_v, m_wo, m_w1, m_w3, m_w2;
        bool ok = make_map(enc, &m_wq, wq, 4096, 512, 64, 64, CU_TENSOR_MAP_SWIZZLE_128B) &&
                  make_map(enc, &m_v, vc, 128, (uint64_t)kHQ * kSK, 64, 64, CU_TENSOR_MAP_SWIZZLE_128B) &&
                  make_map(enc, &m_wo, wo, 512, 4096, 64, 32, CU_TENSOR_MAP_SWIZZLE_128B) &&
                  make_map(enc, &m_w1, w1, kF, 512, 32, 128, CU_TENSOR_MAP_SWIZZLE_64B) &&
                  make_map(enc, &m_w3, w3, kF, 512, 32, 128, CU_TENSOR_MAP_SWIZZLE_64B) &&
                  make_map(enc, &m_w2, w2, 512, kF, 64, 32, CU_TENSOR_MAP_SWIZZLE_128B);
        if (ok) {
            fused_kernel<<<kNCTA, kNTHR, SMEM_BYTES, s>>>(kc, x0, out, g_sched, m_wq, m_v, m_wo, m_w1, m_w3, m_w2);
            return;
        }
    }
    for (int layer = 0; layer < 2; layer++) {
        fb_ln<<<1, 512, 0, s>>>(x0, layer == 0);
        fb_attn<<<kHQ, 1024, 0, s>>>(kc, vc, wq);
        fb_down<<<8, 64, 0, s>>>(wo, 1024, 4096, nullptr);
        fb_ln<<<1, 512, 0, s>>>(x0, 0);
        fb_up<<<(kF + 63) / 64, 64, 0, s>>>(w1, w3);
        fb_down<<<8, 64, 0, s>>>(w2, 5120, kF, layer == 1 ? out : nullptr);
    }
}
```

```cpp
#include <cuda_runtime.h>
#include <cuda_bf16.h>
#include <cuda.h>
#include <stdint.h>

#define P_XST 5

namespace {

constexpr int kD = 512, kHQ = 32, kDH = 128, kSK = 4096, kW = 1024, kF = 1376;
constexpr int kNCTA = 128, kNTHR = 384;
constexpr int kNFFN = 43;

struct Sched {
    int t[16];
    int dar[8];
};

struct Maps { CUtensorMap m[6]; };

constexpr uint32_t OFF_WQ = 0;
constexpr uint32_t OFF_WO = 65536;
constexpr uint32_t OFF_W2 = 131072;
constexpr uint32_t OFF_W1 = 147456;
constexpr uint32_t OFF_W3 = 163840;
constexpr uint32_t OFF_V = OFF_W2;
constexpr uint32_t OFF_XS = 196608;
constexpr uint32_t OFF_ONE = OFF_XS + 576;
constexpr uint32_t OFF_XF = OFF_XS + 1152;
constexpr uint32_t OFF_HP = OFF_XF + 512;
constexpr uint32_t OFF_QP = OFF_HP + 2048;
constexpr uint32_t OFF_QS = OFF_QP + 2048;
constexpr uint32_t OFF_OS = OFF_QS + 256;
constexpr uint32_t OFF_PS = OFF_QS + 1152;
constexpr uint32_t OFF_ZP = OFF_PS + 576;
constexpr uint32_t OFF_MS = OFF_ZP + 576;
constexpr uint32_t OFF_HS = OFF_QS + 512;
constexpr uint32_t OFF_RS = OFF_MS + 64;
constexpr uint32_t OFF_PHI = OFF_RS + 32;
constexpr uint32_t OFF_EP = OFF_PHI + 16;
constexpr uint32_t OFF_DL = OFF_EP + 16;
constexpr uint32_t OFF_MB = OFF_DL + 16;
constexpr uint32_t OFF_TAB = OFF_MB + 256;
constexpr uint32_t SMEM_USED = OFF_TAB + 16384;
constexpr uint32_t SMEM_BYTES = SMEM_USED + 1024 + 256;
enum { MB_K = 0, MB_KFREE, MB_VFREE, MB_WQ, MB_V0  , MB_WO0 = MB_V0 + 4  , MB_W130 = MB_WO0 + 4  , MB_W2 = MB_W130 + 2,
       MB_QX, MB_HX, MB_OX, MB_COUNT };
enum { B_X = 1, B_S, B_H, B_RED, B_Q, B_ST };

__device__ __align__(256) float g_ar_raw[8192 + 8192];
__device__ __align__(256) unsigned g_epoch_line[64];
__device__ __align__(256) unsigned g_flag_line[64];
__device__ float g_fb[8192];
#define TS(i)
#define TW(i)
#define TWD(i, dep)

__device__ __forceinline__ uint32_t smem_u32(const void* p) { return (uint32_t)__cvta_generic_to_shared(p); }
__device__ __forceinline__ void mbar_init(uint32_t bar, int cnt) { asm volatile("mbarrier.init.shared::cta.b64 [%0], %1;" :: "r"(bar), "r"(cnt) : "memory"); }
__device__ __forceinline__ void mbar_expect(uint32_t bar, uint32_t bytes) { asm volatile("mbarrier.arrive.expect_tx.shared::cta.b64 _, [%0], %1;" :: "r"(bar), "r"(bytes) : "memory"); }
__device__ __forceinline__ void mbar_arrive(uint32_t bar) { asm volatile("mbarrier.arrive.shared::cta.b64 _, [%0];" :: "r"(bar) : "memory"); }
__device__ __forceinline__ void mbar_wait(uint32_t bar, uint32_t ph = 0) {
    for (int i = 0; i < (1 << 20); i++) {
        uint32_t ok;
        asm volatile("{\n.reg .pred p;\nmbarrier.try_wait.parity.shared::cta.b64 p, [%1], %2;\nselp.u32 %0, 1, 0, p;\n}" : "=r"(ok) : "r"(bar), "r"(ph) : "memory");
        if (ok) break;
    }
}
__device__ __forceinline__ void bar_sync(int id, int n) { asm volatile("bar.sync %0, %1;" :: "r"(id), "r"(n) : "memory"); }
__device__ __forceinline__ void bar_arrive(int id, int n) { asm volatile("bar.arrive %0, %1;" :: "r"(id), "r"(n) : "memory"); }
__device__ __forceinline__ void tma2d(uint32_t dst, const CUtensorMap* tm, int c0, int c1, uint32_t bar) {
    asm volatile("cp.async.bulk.tensor.2d.shared::cluster.global.mbarrier::complete_tx::bytes [%0], [%1, {%3, %4}], [%2];"
                 :: "r"(dst), "l"((uint64_t)tm), "r"(bar), "r"(c0), "r"(c1) : "memory");
}
__device__ __forceinline__ void ldsm4t(uint32_t* r, uint32_t addr) {
    asm volatile("ldmatrix.sync.aligned.m8n8.x4.trans.shared.b16 {%0,%1,%2,%3}, [%4];" : "=r"(r[0]), "=r"(r[1]), "=r"(r[2]), "=r"(r[3]) : "r"(addr) : "memory");
}
__device__ __forceinline__ void mma16(float* c, uint32_t a0, uint32_t a1, uint32_t a2, uint32_t a3, uint32_t b0, uint32_t b1) {
    asm volatile("mma.sync.aligned.m16n8k16.row.col.f32.bf16.bf16.f32 {%0,%1,%2,%3}, {%4,%5,%6,%7}, {%8,%9}, {%0,%1,%2,%3};"
                 : "+f"(c[0]), "+f"(c[1]), "+f"(c[2]), "+f"(c[3]) : "r"(a0), "r"(a1), "r"(a2), "r"(a3), "r"(b0), "r"(b1));
}
__device__ __forceinline__ uint4 lds128(uint32_t a) { uint4 v; asm volatile("ld.shared.v4.u32 {%0,%1,%2,%3}, [%4];" : "=r"(v.x), "=r"(v.y), "=r"(v.z), "=r"(v.w) : "r"(a) : "memory"); return v; }
__device__ __forceinline__ float4 lds128f(uint32_t a) { float4 v; asm volatile("ld.shared.v4.f32 {%0,%1,%2,%3}, [%4];" : "=f"(v.x), "=f"(v.y), "=f"(v.z), "=f"(v.w) : "r"(a) : "memory"); return v; }
__device__ __forceinline__ void sts16(uint32_t a, uint32_t v) { asm volatile("st.shared.u16 [%0], %1;" :: "r"(a), "h"((uint16_t)v) : "memory"); }
__device__ __forceinline__ void sts32(uint32_t a, uint32_t v) { asm volatile("st.shared.u32 [%0], %1;" :: "r"(a), "r"(v) : "memory"); }
__device__ __forceinline__ void send_pair(uint32_t a, uint32_t rbar, float v0, float v1, uint32_t mode) {
    asm volatile("{\n.reg .pred pl, pr;\nsetp.eq.u32 pl, %4, 1;\nsetp.eq.u32 pr, %4, 2;\n"
                 "@pr st.async.shared::cluster.mbarrier::complete_tx::bytes.v2.f32 [%0], {%1,%2}, [%3];\n"
                 "@pl st.shared.v2.f32 [%0], {%1,%2};\n}" :: "r"(a), "f"(v0), "f"(v1), "r"(rbar), "r"(mode) : "memory");
}
__device__ __forceinline__ void send_word(uint32_t a, uint32_t rbar, uint32_t v, uint32_t mode) {
    asm volatile("{\n.reg .pred pl, pr;\nsetp.eq.u32 pl, %3, 1;\nsetp.eq.u32 pr, %3, 2;\n"
                 "@pr st.async.shared::cluster.mbarrier::complete_tx::bytes.b32 [%0], %1, [%2];\n"
                 "@pl st.shared.b32 [%0], %1;\n}" :: "r"(a), "r"(v), "r"(rbar), "r"(mode) : "memory");
}
__device__ __forceinline__ void red_pair(const void* p, float v, uint32_t on) {
    asm volatile("{\n.reg .pred p;\nsetp.ne.u32 p, %3, 0;\n@p red.relaxed.gpu.global.add.v2.f32 [%0], {%1,%2};\n}" :: "l"(p), "f"(v), "f"(1.f), "r"(on) : "memory");
}
__device__ __forceinline__ float fsel(bool p, float a, float b) { float r; asm("{\n.reg .pred q;\nsetp.ne.u32 q, %3, 0;\nselp.f32 %0, %1, %2, q;\n}" : "=f"(r) : "f"(a), "f"(b), "r"((uint32_t)p)); return r; }
__device__ __forceinline__ void sts128(uint32_t a, uint32_t x, uint32_t y, uint32_t z, uint32_t w) { asm volatile("st.shared.v4.u32 [%0], {%1,%2,%3,%4};" :: "r"(a), "r"(x), "r"(y), "r"(z), "r"(w) : "memory"); }
__device__ __forceinline__ uint2 lds64(uint32_t a) { uint2 v; asm volatile("ld.shared.v2.u32 {%0,%1}, [%2];" : "=r"(v.x), "=r"(v.y) : "r"(a) : "memory"); return v; }
__device__ __forceinline__ uint4 lds128v(uint32_t a) { uint4 v; asm volatile("ld.volatile.shared.v4.u32 {%0,%1,%2,%3}, [%4];" : "=r"(v.x), "=r"(v.y), "=r"(v.z), "=r"(v.w) : "r"(a) : "memory"); return v; }
__device__ __forceinline__ uint32_t lds32(uint32_t a) { uint32_t v; asm volatile("ld.shared.u32 %0, [%1];" : "=r"(v) : "r"(a) : "memory"); return v; }
__device__ __forceinline__ float rsq(float x) { float r; asm("rsqrt.approx.ftz.f32 %0, %1;" : "=f"(r) : "f"(x)); return r; }
__device__ __forceinline__ float rcp(float x) { float r; asm("rcp.approx.ftz.f32 %0, %1;" : "=f"(r) : "f"(x)); return r; }
__device__ __forceinline__ const char* mk64(uint32_t lo, uint32_t hi) { return (const char*)(((uint64_t)hi << 32) | lo); }
__device__ __forceinline__ unsigned gtime() { unsigned t; asm volatile("mov.u32 %0, %%globaltimer_lo;" : "=r"(t)); return t; }
__device__ __forceinline__ unsigned clk() { unsigned t; asm volatile("mov.u32 %0, %%clock;" : "=r"(t)); return t; }
__device__ __forceinline__ void spin(int n) { const unsigned t = clk(); while ((int)(clk() - t) < n) {} }
__device__ __forceinline__ void pace(unsigned t0, int ns) { for (int i = 0; i < (1 << 16) && (int)(gtime() - t0) < ns; i++) {} }
__device__ __forceinline__ uint4 ld_poll(const void* p) {
    unsigned long long a, b;
    asm volatile("ld.relaxed.gpu.global.v2.b64 {%0,%1}, [%2];" : "=l"(a), "=l"(b) : "l"(p) : "memory");
    return make_uint4((uint32_t)a, (uint32_t)(a >> 32), (uint32_t)b, (uint32_t)(b >> 32));
}
__device__ __forceinline__ void st_pkt(const void* p, uint32_t v, uint32_t tag, uint32_t on) {
    asm volatile("{\n.reg .pred p;\n.reg .b64 d;\nsetp.ne.u32 p, %3, 0;\nmov.b64 d, {%1,%2};\n@p st.relaxed.gpu.global.b64 [%0], d;\n}" :: "l"(p), "r"(v), "r"(tag), "r"(on) : "memory");
}
__device__ __forceinline__ uint32_t pack_bf16(float lo, float hi) {
    uint32_t r; asm("cvt.rn.bf16x2.f32 %0, %1, %2;" : "=r"(r) : "f"(hi), "f"(lo)); return r;
}
__device__ __forceinline__ float bf_lo(uint32_t v) { return __uint_as_float(v << 16); }
__device__ __forceinline__ float bf_hi(uint32_t v) { return __uint_as_float(v & 0xffff0000u); }
__device__ __forceinline__ float ex2(float x) { float r; asm("ex2.approx.ftz.f32 %0, %1;" : "=f"(r) : "f"(x)); return r; }
__device__ __forceinline__ float warp_max(float v) {
    int i = __float_as_int(v);
    i ^= (i >> 31) & 0x7fffffff;
    i = __reduce_max_sync(0xffffffffu, i);
    i ^= (i >> 31) & 0x7fffffff;
    return __int_as_float(i);
}
__device__ __forceinline__ uint32_t ar_off(int k, int ln) {
    return (ln >> 1) * 1024 + (ln & 1) * 256 + (k & 1) * 128 + (k >> 1) * 512;
}

#define MMA4(A, i0, i1, i2, i3, b, d) \
    mma16(a0, A[i0], A[i0 + 1], A[i0 + 2], A[i0 + 3], b.x, b.y); \
    mma16(a1, A[i1], A[i1 + 1], A[i1 + 2], A[i1 + 3], b.z, b.w); \
    mma16(a2, A[i2], A[i2 + 1], A[i2 + 2], A[i2 + 3], d.x, d.y); \
    mma16(a3, A[i3], A[i3 + 1], A[i3 + 2], A[i3 + 3], d.z, d.w);
#define ZACC float a0[4] = {0.f, 0.f, 0.f, 0.f}, a1[4] = {0.f, 0.f, 0.f, 0.f}, a2[4] = {0.f, 0.f, 0.f, 0.f}, a3[4] = {0.f, 0.f, 0.f, 0.f}
#define LN_STATS \
    const float4 r0_ = lds128f(sb + OFF_RS), r1_ = lds128f(sb + OFF_RS + 16); \
    const float mean_ = ((r0_.x + r0_.z) + (r1_.x + r1_.z)) * (1.f / kD); \
    const float rstd = rsq(fmaxf(fmaf(-mean_, mean_, fmaf((r0_.y + r0_.w) + (r1_.y + r1_.w), 1.f / kD, 1e-5f)), 1e-5f)); \
    const float nmr = -mean_ * rstd
#define PICK4C(k) (fsel(t2, fsel(t1, a2[2 + k], a2[k]), fsel(t1, a0[2 + k], a0[k])) + fsel(t2, fsel(t1, a3[2 + k], a3[k]), fsel(t1, a1[2 + k], a1[k])))
#define PICK4 (fsel(t2, fsel(t1, a2[2], a2[0]), fsel(t1, a0[2], a0[0])) + fsel(t2, fsel(t1, a3[2], a3[0]), fsel(t1, a1[2], a1[0])))

__global__ void __cluster_dims__(2, 1, 1) __launch_bounds__(kNTHR, 1)
fused_kernel(const __nv_bfloat16* __restrict__ kc, const __nv_bfloat16* __restrict__ x0, __nv_bfloat16* __restrict__ out,
             const __grid_constant__ Sched sc, const __grid_constant__ Maps tm) {
    extern __shared__ uint8_t smem_raw[];
    const uint32_t sb = (smem_u32(smem_raw) + 1023u) & ~1023u;
    const uint32_t mb = sb + OFF_MB;
    const int tid = threadIdx.x;
    const int c = blockIdx.x;
    asm volatile("{\n.reg .pred p;\nsetp.eq.u32 p, %0, 352;\n"
                 "@p mbarrier.init.shared::cta.b64 [%1], 1;\n"
                 "@p fence.mbarrier_init.release.cluster;\n"
                 "@p mbarrier.arrive.expect_tx.shared::cta.b64 _, [%1], 65536;\n"
                 "@p cp.async.bulk.shared::cluster.global.mbarrier::complete_tx::bytes [%2], [%3], 65536, [%1];\n}"
                 :: "r"(tid), "r"(mb + MB_K * 8), "r"(sb + OFF_WO),
                    "l"((const char*)kc + ((size_t)(c >> 2) << 20) + (size_t)((kSK - kW) * kDH * 2 + (c & 3) * 65536)) : "memory");
    const unsigned t0 = gtime();
    const int warp = __shfl_sync(0xffffffffu, tid >> 5, 0), lane = tid & 31;
    const int h = c >> 2, j = c & 3, r = c & 1, p = c >> 1;
    const int g = lane >> 2, t = lane & 3;
    const bool ffn = p < kNFFN;
    char* const ar = (char*)(((uintptr_t)g_ar_raw + 32767) & ~(uintptr_t)32767);
    uint32_t rsb;
    asm("mapa.shared::cluster.u32 %0, %1, %2;" : "=r"(rsb) : "r"(sb), "r"(r ^ 1));

    if (warp >= 8) {
        asm volatile("setmaxnreg.dec.sync.aligned.u32 40;");
        const int cw = warp - 8;
        if (cw == 3) {
            if (lane >= 1 && lane < MB_COUNT) {
                const bool tma = lane >= MB_WQ && lane <= MB_W2;
                mbar_init(mb + lane * 8, tma ? 1 : lane == MB_OX ? 9 : 8);
                if (tma) mbar_expect(mb + lane * 8, lane == MB_WQ ? 65536 : 16384);
            }
            asm volatile("fence.mbarrier_init.release.cluster;" ::: "memory");
            __syncwarp();
        } else if (cw == 2 && lane < 6) {
            asm volatile("prefetch.tensormap [%0];" :: "l"((uint64_t)&tm.m[lane]) : "memory");
        }
        __syncwarp();
        asm volatile("barrier.cluster.arrive.relaxed.aligned;" ::: "memory");
        uint32_t xp = *(const uint32_t*)(x0 + r * 256 + cw * 64 + lane * 2);
        uint32_t xq = *(const uint32_t*)(x0 + (r ^ 1) * 256 + cw * 64 + lane * 2);
        sts32(sb + OFF_ONE + cw * 128 + lane * 4, 0x3F803F80u);
        sts32(sb + OFF_ZP + cw * 128 + lane * 4, 0u);
        if (lane < 4) sts32(sb + OFF_DL + lane * 4, sc.dar[ffn || lane == 0 ? lane : lane + 4]);
        const int dos2 = sc.dar[4];
        __syncwarp();
        const uint32_t xs_a = __shfl_sync(0xffffffffu, sb + OFF_XS + cw * 128 + ((lane >> 4) & 1) * 64 + (lane & 3) * 16 + ((lane >> 3) & 1) * 8 + ((lane >> 2) & 1) * 4, lane);
        const uint32_t xf_a = __shfl_sync(0xffffffffu, sb + OFF_XF + cw * 128 + lane * 4, lane);
        const uint32_t ar_o = __shfl_sync(0xffffffffu, ar_off(0, r * 16 + cw * 4 + (lane >> 3)) + (lane & 7) * 16, lane);

        auto xstage = [&](int st) -> bool {
            const uint32_t tg = __float_as_uint((st & 1) ? 64.f : (float)kNFFN);
            const bool act = ffn || !(st & 1);
            const char* a = ar + (ar_o + ((st - 1) & 1) * 128 + ((st - 1) >> 1) * 512);
            const char* a2 = (const char*)((uintptr_t)a ^ 8192);
            uint4 u = make_uint4(0, tg, 0, tg);
            if (st > 0) {
                const int dar = lds32(sb + OFF_DL + st * 4);
                if (ffn || (st & 1)) bar_sync(B_RED, 384);
                if (!ffn) {
                    if (st == 3) return false;
                    if (st == 2) {
                        const unsigned want = lds32(sb + OFF_EP) + 1;
#pragma unroll 1
                        for (int it = 0; it < (1 << 18); it++) {
                            unsigned fl;
                            asm volatile("ld.relaxed.gpu.global.u32 %0, [%1];" : "=r"(fl) : "l"(ar + 24576 + (c - 2 * kNFFN) * 128) : "memory");
                            if (__all_sync(0xffffffffu, fl == want)) break;
                        }
                    }
                }
                spin(dar);
                if (st >= 2 && cw == 0) TS(60 + st);
                uint4 v;
#pragma unroll 1
                for (int it = 0; it < (1 << 18); it++) {
                    v = ld_poll(a);
                    u = ld_poll(a2);
                    if (__all_sync(0xffffffffu, v.y == tg && v.w == tg)) break;
                }
                const uint32_t d = pack_bf16(__uint_as_float(v.x), __uint_as_float(v.z));
                xp = pack_bf16(bf_lo(xp) + bf_lo(d), bf_hi(xp) + bf_hi(d));
            }
            if (act) {
                sts32(xs_a, xp);
                sts32(xf_a, xp);
                bar_arrive(B_X, 384);
            }
            if (cw == 0) TS(1 + st * 6);
            if (st >= 2) TS(46 + st * 4 + cw);
#pragma unroll 1
            for (int it = 0; it < (1 << 18); it++) {
                if (__all_sync(0xffffffffu, u.y == tg && u.w == tg)) break;
                u = ld_poll(a2);
            }
            const uint32_t d = pack_bf16(__uint_as_float(u.x), __uint_as_float(u.z));
            xq = pack_bf16(bf_lo(xq) + bf_lo(d), bf_hi(xq) + bf_hi(d));
            if (!act) return false;
            const float xa = bf_lo(xp), xb = bf_hi(xp), xc = bf_lo(xq), xd = bf_hi(xq);
            float s1 = (xa + xb) + (xc + xd), s2 = fmaf(xa, xa, xb * xb) + fmaf(xc, xc, xd * xd);
#pragma unroll
            for (int o = 16; o > 0; o >>= 1) { s1 += __shfl_xor_sync(0xffffffffu, s1, o); s2 += __shfl_xor_sync(0xffffffffu, s2, o); }
            asm volatile("st.shared.v2.f32 [%0], {%1,%2};" :: "r"(sb + OFF_RS + cw * 8), "f"(s1), "f"(s2) : "memory");
            if (cw == 0) bar_sync(B_ST, 128); else bar_arrive(B_ST, 128);
            return true;
        };
        auto phi_stage = [&](const char* sp, uint32_t tag, int layer) {
            uint4 e0, e1, e2, e3;
#pragma unroll 1
            for (int it = 0; it < (1 << 18); it++) {
                e0 = ld_poll(sp); e1 = ld_poll(sp + 32); e2 = ld_poll(sp + 64); e3 = ld_poll(sp + 96);
                if (__all_sync(0xffffffffu, e0.y == tag && e0.w == tag && e1.y == tag && e1.w == tag && e2.y == tag && e2.w == tag && e3.y == tag && e3.w == tag)) break;
            }
            const float Mh = fmaxf(fmaxf(__uint_as_float(e0.x), __uint_as_float(e1.x)), fmaxf(__uint_as_float(e2.x), __uint_as_float(e3.x)));
            const float w0 = ex2(__uint_as_float(e0.x) - Mh), w1 = ex2(__uint_as_float(e1.x) - Mh), w2 = ex2(__uint_as_float(e2.x) - Mh), w3 = ex2(__uint_as_float(e3.x) - Mh);
            const float il = rcp(fmaf(w0, __uint_as_float(e0.z), w1 * __uint_as_float(e1.z)) + fmaf(w2, __uint_as_float(e2.z), w3 * __uint_as_float(e3.z)));
            sts128(sb + OFF_PHI, __float_as_uint(((j & 2) ? w2 : w0) * il), __float_as_uint(((j & 2) ? w3 : w1) * il), layer + 1, 0);
        };

        if (cw == 0) {
            asm volatile("barrier.cluster.wait.acquire.aligned;" ::: "memory");
            const uint32_t l16 = __shfl_sync(0xffffffffu, sb + OFF_HP + lane * 16, lane);
            const uint32_t qs_a = __shfl_sync(0xffffffffu, sb + OFF_QS + g * 32 + t * 4, lane);
            const uint32_t hs_a = __shfl_sync(0xffffffffu, sb + OFF_HS + ((lane & 7) >> 1) * 16 + (lane >> 4) * 8 + ((lane >> 3) & 1) * 4 + (lane & 1) * 2, lane);
            float cs[4] = {0.f, 0.f, 0.f, 0.f}, c1 = 0.f, c3 = 0.f;
#pragma unroll 1
            for (int st = 0; st < 4; st++) {
                if (!xstage(st)) continue;
                LN_STATS;
                if (st >= 2) TS(50 + st);
                if (!(st & 1)) {
                    mbar_wait(mb + MB_QX * 8, st >> 1);
                    TS(2 + st * 6);
                    const float4 a = lds128f(l16 + 2048), b = lds128f(l16 + 2048 + 512);
                    if (st == 0) {
                        const float4 u = lds128f(l16 + 2048 + 1024), w = lds128f(l16 + 2048 + 1536);
                        cs[0] = u.x + w.x; cs[1] = u.y + w.y; cs[2] = u.z + w.z; cs[3] = u.w + w.w;
                    }
                    const float q0 = fmaf(rstd, a.x + b.x, nmr * cs[0]), q8 = fmaf(rstd, a.y + b.y, nmr * cs[1]);
                    const float q1 = fmaf(rstd, a.z + b.z, nmr * cs[2]), q9 = fmaf(rstd, a.w + b.w, nmr * cs[3]);
                    const uint32_t qa = pack_bf16(q0, q1), qb = pack_bf16(q8, q9);
                    sts32(qs_a, qa); sts32(qs_a + 16, qb); sts32(qs_a + 576, qa); sts32(qs_a + 592, qb);
                    bar_arrive(B_Q, 288);
                    if (st == 2) TS(35);
                    if (st == 0) {
                        const unsigned want = lds32(sb + OFF_EP) + 1;
#pragma unroll 1
                        for (int it = 0; it < (1 << 18); it++) {
                            unsigned fl;
                            asm volatile("ld.acquire.gpu.global.u32 %0, [%1];" : "=r"(fl) : "l"(g_flag_line + (lane & 15)) : "memory");
                            if (__all_sync(0xffffffffu, fl == want)) break;
                        }
                    }
                    if (lane == 0) mbar_arrive(mb + MB_OX * 8);
                    __syncwarp();
                } else {
                    mbar_wait(mb + MB_HX * 8, st >> 1);
                    TS(2 + st * 6);
                    const float4 a = lds128f(l16), b = lds128f(l16 + 512);
                    if (st == 1) {
                        const float4 u = lds128f(l16 + 1024), w = lds128f(l16 + 1536);
                        c1 = (u.x + u.z) + (w.x + w.z); c3 = (u.y + u.w) + (w.y + w.w);
                    }
                    const float gate = fmaf(rstd, (a.x + a.z) + (b.x + b.z), nmr * c1), up = fmaf(rstd, (a.y + a.w) + (b.y + b.w), nmr * c3);
                    const float hv = gate * up * rcp(1.f + ex2(-1.4426950408889634f * gate));
                    const uint32_t hb = pack_bf16(hv, 0.f);
                    sts16(hs_a, hb); sts16(hs_a + 576, hb);
                    bar_arrive(B_H, 288);
                    TS(3 + st * 6);
                }
            }
        } else if (cw == 1) {
            unsigned epoch;
            asm volatile("ld.relaxed.gpu.global.u32 %0, [%1];" : "=r"(epoch) : "l"(g_epoch_line) : "memory");
            const char* const my_st = ar + 16384 + c * 32 + t * 8 + (g & 1) * 4096;
            st_pkt(my_st, 0, 0, lane < 8);
            sts32(sb + OFF_MS + 32 + g * 4, 0x80000000u);
            if (lane == 0) { sts128(sb + OFF_PHI, 0, 0, 0, 0); sts32(sb + OFF_EP, epoch); }
            asm volatile("barrier.cluster.wait.acquire.aligned;" ::: "memory");
#pragma unroll 1
            for (int st = 0; st < 4; st++) {
                if (!xstage(st) || (st & 1)) continue;
                const uint32_t tag = epoch * 2 + (st >> 1) + 1;
                bar_sync(B_S, 320);
                const uint4 pv = lds128(sb + OFF_PS + lane * 16);
                const float4 m0 = lds128f(sb + OFF_MS), m1 = lds128f(sb + OFF_MS + 16);
                const float mg = __uint_as_float(lds32(sb + OFF_MS + g * 4));
                const float M = fmaxf(fmaxf(fmaxf(m0.x, m0.y), fmaxf(m0.z, m0.w)), fmaxf(fmaxf(m1.x, m1.y), fmaxf(m1.z, m1.w)));
                const float al = ex2(mg - M);
                sts32(sb + OFF_MS + 32 + g * 4, (__float_as_uint(al) & 0x7fffffffu) | ((uint32_t)st << 30));
                const float lp = (((bf_lo(pv.x) + bf_hi(pv.x)) + (bf_lo(pv.y) + bf_hi(pv.y))) + ((bf_lo(pv.z) + bf_hi(pv.z)) + (bf_lo(pv.w) + bf_hi(pv.w)))) * (al * 8388608.f);
                const float L = __uint2float_rn(__reduce_add_sync(0xffffffffu, __float2uint_rn(lp))) * (1.f / 8388608.f);
                st_pkt(my_st, __float_as_uint((lane & 1) ? L : M), tag, lane < 8);
                TS(3 + st * 6);
                spin(lds32(sb + OFF_DL));
                phi_stage(ar + 16384 + h * 128, tag, st >> 1);
                TS(6 + st * 6);
            }
        } else if (cw == 2) {
            unsigned epoch;
            asm volatile("ld.relaxed.gpu.global.u32 %0, [%1];" : "=r"(epoch) : "l"(g_epoch_line) : "memory");
            st_pkt(ar + 24576 + c * 128 + lane * 8, 0, 0, lane < 4 && c < kNCTA - 2 * kNFFN);
            if (c < 16) {
                asm volatile("st.relaxed.gpu.global.v4.u32 [%0], {%1,%1,%1,%1};" :: "l"(ar + c * 1024 + lane * 16), "r"(0) : "memory");
                asm volatile("st.relaxed.gpu.global.v4.u32 [%0], {%1,%1,%1,%1};" :: "l"(ar + c * 1024 + 512 + lane * 16), "r"(0) : "memory");
                __threadfence();
                __syncwarp();
                if (lane == 0) asm volatile("st.relaxed.gpu.global.u32 [%0], %1;" :: "l"(g_flag_line + c), "r"(epoch + 1) : "memory");
            }
            asm volatile("barrier.cluster.wait.acquire.aligned;" ::: "memory");
#pragma unroll 1
            for (int st = 0; st < 4; st++) {
                if (!xstage(st)) continue;
                if (st & 1) {
                    if (st == 1 && c < kNCTA - 2 * kNFFN) {
                        mbar_wait(mb + MB_W2 * 8);
                        mbar_wait(mb + MB_HX * 8);
                        st_pkt(ar + 24576 + c * 128 + lane * 8, epoch + 1, 0, lane < 4);
                    }
                    continue;
                }
                bar_sync(B_S, 320);
                spin(dos2);
                phi_stage(ar + 16384 + 4096 + h * 128, epoch * 2 + (st >> 1) + 1, st >> 1);
                if (st == 2) TS(23);
            }
        } else {
            const int ty = lane >> 2, q = lane & 3;
            const bool w13 = ty == 3 && q < 2;
            const uint32_t c_dst = sb + (ty == 0 ? OFF_WQ + q * 8192 : ty == 1 ? OFF_V + q * 16384 : ty == 2 ? OFF_WO + q * 4096 : w13 ? OFF_W1 + q * 8192 : OFF_W2);
            const uint32_t c_dd = ty == 0 ? 32768 : ty == 1 ? 8192 : ty == 2 || w13 ? 16384 : 4096;
            const int c_x = ty == 0 ? h * 128 : ty == 1 ? 0 : w13 ? p * 32 : r * 256;
            const int c_y = ty == 0 ? r * 256 + q * 64 : ty == 1 ? h * kSK + (kSK - kW) + j * 256 + q * 64 : ty == 2 ? h * 128 + q * 32 : w13 ? r * 256 + q * 128 : p * 32;
            const uint32_t c_inf = (uint32_t)sc.t[lane & 15] | ((ty < 3 || w13 ? ty : 5) << 16) | ((ty < 2 || w13 ? 2 : 4) << 20) | (w13 ? 1u << 24 : 0u);
            const int nch = ffn ? 15 : 12;
#pragma unroll 1
            for (int i = 0; i < nch; i++) {
                const uint32_t dst = __shfl_sync(0xffffffffu, c_dst, i), dd = __shfl_sync(0xffffffffu, c_dd, i), inf = __shfl_sync(0xffffffffu, c_inf, i);
                const int x = __shfl_sync(0xffffffffu, c_x, i), y = __shfl_sync(0xffffffffu, c_y, i);
                if (i == P_XST) {
                    asm volatile("barrier.cluster.wait.acquire.aligned;" : "+r"(xp), "+r"(xq) :: "memory");
                    xstage(0);
                }
                if (i >= 8) mbar_wait(mb + (i < 12 ? MB_KFREE : MB_VFREE) * 8);
                if (i == 0) TS(22);
                pace(t0, inf & 0xffff);
                if (lane < (int)((inf >> 20) & 7))
                    tma2d(dst + lane * dd, &tm.m[((inf >> 16) & 7) + (inf >> 24) * lane], x + ((inf >> 24) ? 0 : lane * 64), y, mb + (MB_WQ + max(i - 3, 0)) * 8);
                __syncwarp();
            }
#pragma unroll 1
            for (int st = 1; st < 4; st++) xstage(st);
        }
    } else {
        asm volatile("setmaxnreg.inc.sync.aligned.u32 232;");
        asm volatile("barrier.cluster.arrive.relaxed.aligned;" ::: "memory");
        const int w = warp;
        const bool t1 = t & 1, t2 = t & 2, l0 = lane == 0;
        uint32_t KR[64], VR[64], S[64];
        {
            const int mt = w & 3, kh = w >> 2, ln = w + 8 * (t >> 1), cc = g + 8 * (t & 1);
            const uint32_t snd = ((t & 1) ? rsb : sb) + r * 512 + (t >> 1) * 1024;
            const uint64_t arc = (uint64_t)(ar + ar_off(0, r * 16 + ln) + cc * 8), op = (uint64_t)(out + r * 256 + ln * 16 + cc);
            const uint32_t sn2 = ((t & 1) ? rsb : sb) + r * 576;
            sts128(sb + OFF_TAB + tid * 16, snd + OFF_QP + w * 64 + g * 8, rsb + OFF_MB + MB_QX * 8, 0, 0);
            sts128(sb + OFF_TAB + 4096 + tid * 16, (uint32_t)arc, (uint32_t)(arc >> 32), snd + OFF_HP + (mt * 8 + g) * 16 + kh * 8, rsb + OFF_MB + MB_HX * 8);
            sts128(sb + OFF_TAB + 8192 + tid * 16, (uint32_t)op, (uint32_t)(op >> 32), sb + OFF_XF + (ln * 16 + cc) * 2,
                   sb + OFF_W1 + ((lane >> 3) & 1) * 16384 + (kh * 128 + (lane >> 4) * 8 + (lane & 7)) * 64 + ((mt ^ ((lane >> 1) & 3)) << 4));
            sts128(sb + OFF_TAB + 12288 + tid * 16, sb + OFF_PS + (w * 4 + (g >> 1)) * 16 + t * 4 + (g & 1) * 2, sb + ((g & 1) ? OFF_PS : OFF_ZP) + 64 + t * 16,
                   sn2 + OFF_OS + (w >> 1) * 64 + (g & 3) * 16 + (w & 1) * 8 + (g >> 2) * 4, rsb + OFF_MB + MB_OX * 8);
        }
        const uint32_t xb = __shfl_sync(0xffffffffu, sb + ((g & 1) ? OFF_ONE : OFF_XS) + t * 16, lane);
        const uint32_t tab = __shfl_sync(0xffffffffu, sb + OFF_TAB + tid * 16, lane);
        const uint32_t lm = __shfl_sync(0xffffffffu, sb + ((lane >> 4) * 8 + (lane & 7)) * 128 + ((((w & 3) * 2 + ((lane >> 3) & 1)) ^ (lane & 7)) << 4), lane);
        const uint32_t wh = w >> 2;
        asm volatile("barrier.cluster.wait.acquire.aligned;" ::: "memory");
        mbar_wait(mb + MB_K * 8);
        if (w == 0) TS(24);
        {
            const uint32_t kp = sb + OFF_WO + (w * 32 + g) * 256 + t * 16;
#pragma unroll
            for (int rr = 0; rr < 4; rr++)
#pragma unroll
                for (int i = 0; i < 4; i++) {
                    const uint4 v = lds128(kp + rr * 2048 + i * 64);
                    uint32_t* d = &KR[(rr >> 1) * 32 + i * 8 + (rr & 1)];
                    d[0] = v.x; d[2] = v.y; d[4] = v.z; d[6] = v.w;
                }
        }
        __syncwarp();
        if (l0) mbar_arrive(mb + MB_KFREE * 8);
#pragma unroll
        for (int i = 0; i < 64; i++) VR[i] = 0;

#pragma unroll 1
        for (int layer = 0; layer < 2; layer++) {
            const uint32_t smode = (!t2 || layer == 0) ? (t1 ? 2u : 1u) : 0u, smode2 = t2 ? 0u : (t1 ? 2u : 1u);
            const uint32_t lm_wo = lm + OFF_WO + wh * 16384;
            mbar_wait(mb + MB_WQ * 8);
            if (w == 0 && layer == 0) TS(25);
#pragma unroll
            for (int s = 0; s < 16; s++) ldsm4t(&S[s * 4], lm + OFF_WQ + wh * 32768 + s * 2048);
            const uint2 T0 = lds64(tab);
            {
                bar_sync(B_X, 384);
                ZACC;
#pragma unroll
                for (int i = 0; i < 4; i++) {
                    const uint4 b = lds128(xb + i * 128), d = lds128(xb + i * 128 + 64);
                    MMA4(S, i * 16, i * 16 + 4, i * 16 + 8, i * 16 + 12, b, d);
                }
                const float v0 = (fsel(t2, a0[1], a0[0]) + fsel(t2, a1[1], a1[0])) + (fsel(t2, a2[1], a2[0]) + fsel(t2, a3[1], a3[0]));
                const float v1 = (fsel(t2, a0[3], a0[2]) + fsel(t2, a1[3], a1[2])) + (fsel(t2, a2[3], a2[2]) + fsel(t2, a3[3], a3[2]));
                send_pair(T0.x, T0.y, v0, v1, smode);
                __syncwarp();
                if (l0) mbar_expect(mb + MB_QX * 8, layer ? 64 : 128);
                TW(2);
            }
#pragma unroll
            for (int s = 0; s < 8; s++) ldsm4t(&S[s * 4], lm_wo + s * 2048);
            const uint4 T3 = lds128(tab + 12288);
            {
                bar_sync(B_Q, 288);
                uint4 b[4];
#pragma unroll
                for (int i = 0; i < 3; i++) b[i] = lds128(xb + (OFF_QS - OFF_XS) + i * 64);
                { const uint2 v = lds64(xb + (OFF_QS - OFF_XS) + 192); b[3].x = v.x; b[3].y = v.y; }
#pragma unroll
                for (int s = 0; s < 4; s++) ldsm4t(&S[32 + s * 4], lm_wo + 32768 + s * 2048);
                __syncwarp();
                { const uint2 v = lds64(xb + (OFF_QS - OFF_XS) + 200); b[3].z = v.x; b[3].w = v.y; }
                ZACC;
#pragma unroll
                for (int i = 0; i < 4; i++) { MMA4(KR, i * 8, i * 8 + 4, 32 + i * 8, 32 + i * 8 + 4, b[i], b[i]); }
                const float sv = PICK4 * (0.08838834764831845f * 1.4426950408889634f);
                TWD(3, sv);
                const float m = warp_max(sv);
                sts16(T3.x, pack_bf16(ex2(sv - m), 0.f));
                if (l0) sts32(sb + OFF_MS + w * 4, __float_as_uint(m));
                TW(4);
            }
            bar_sync(B_S, 320);
            if (layer == 0) {
                const uint32_t vch = (w & 3) * 2 + (g >> 2), vb = sb + OFF_V + wh * 8192 + t * 256 + (g & 3) * 4;
                const uint32_t va0 = vb + ((vch ^ (2 * t)) << 4), va1 = vb + 128 + ((vch ^ (2 * t + 1)) << 4);
#pragma unroll
                for (int q = 0; q < 4; q++) {
                    mbar_wait(mb + (MB_V0 + q) * 8);
#pragma unroll
                    for (int s = 0; s < 8; s++) {
                        const uint32_t e = lds32(va0 + q * 16384 + s * 1024), o = lds32(va1 + q * 16384 + s * 1024);
                        VR[q * 16 + s * 2] = __byte_perm(e, o, 0x5410); VR[q * 16 + s * 2 + 1] = __byte_perm(e, o, 0x7632);
                    }
                    if (q == 2) {
                        __syncwarp();
                        if (l0) mbar_arrive(mb + MB_VFREE * 8);
                    }
                }
                if (w == 0) TS(26);
            }
            {
                const uint32_t pe = xb + (OFF_PS - OFF_XS), po = T3.y;
                uint4 b[8];
#pragma unroll
                for (int i = 0; i < 4; i++) b[i] = lds128(pe + i * 128);
#pragma unroll
                for (int i = 0; i < 4; i++) b[4 + i] = lds128(po + i * 128);
                __syncwarp();
                uint4 ua = lds128v(sb + OFF_MS + 32), ub = lds128v(sb + OFF_MS + 48);
                const uint32_t sgn = (uint32_t)layer << 31;
#define W_OK __all_sync(0xffffffffu, (int)((((ua.x ^ sgn) | (ua.y ^ sgn)) | ((ua.z ^ sgn) | (ua.w ^ sgn))) | (((ub.x ^ sgn) | (ub.y ^ sgn)) | ((ub.z ^ sgn) | (ub.w ^ sgn)))) >= 0)
                const bool wok = W_OK;
                ZACC;
#pragma unroll
                for (int hf = 0; hf < 2; hf++) {
                    mma16(a0, VR[hf * 8 + 0], VR[hf * 8 + 1], VR[hf * 8 + 2], VR[hf * 8 + 3], b[hf * 4 + 0].x, b[hf * 4 + 0].y);
                    mma16(a1, VR[hf * 8 + 16], VR[hf * 8 + 17], VR[hf * 8 + 18], VR[hf * 8 + 19], b[hf * 4 + 1].x, b[hf * 4 + 1].y);
                    mma16(a2, VR[hf * 8 + 32], VR[hf * 8 + 33], VR[hf * 8 + 34], VR[hf * 8 + 35], b[hf * 4 + 2].x, b[hf * 4 + 2].y);
                    mma16(a3, VR[hf * 8 + 48], VR[hf * 8 + 49], VR[hf * 8 + 50], VR[hf * 8 + 51], b[hf * 4 + 3].x, b[hf * 4 + 3].y);
                    mma16(a0, VR[hf * 8 + 4], VR[hf * 8 + 5], VR[hf * 8 + 6], VR[hf * 8 + 7], b[hf * 4 + 0].z, b[hf * 4 + 0].w);
                    mma16(a1, VR[hf * 8 + 20], VR[hf * 8 + 21], VR[hf * 8 + 22], VR[hf * 8 + 23], b[hf * 4 + 1].z, b[hf * 4 + 1].w);
                    mma16(a2, VR[hf * 8 + 36], VR[hf * 8 + 37], VR[hf * 8 + 38], VR[hf * 8 + 39], b[hf * 4 + 2].z, b[hf * 4 + 2].w);
                    mma16(a3, VR[hf * 8 + 52], VR[hf * 8 + 53], VR[hf * 8 + 54], VR[hf * 8 + 55], b[hf * 4 + 3].z, b[hf * 4 + 3].w);
                }
                if (!wok) {
#pragma unroll 1
                    for (int it = 0; it < (1 << 22); it++) {
                        ua = lds128v(sb + OFF_MS + 32); ub = lds128v(sb + OFF_MS + 48);
                        if (W_OK) break;
                    }
                }
                const float4 wa = make_float4(fabsf(__uint_as_float(ua.x)), fabsf(__uint_as_float(ua.y)), fabsf(__uint_as_float(ua.z)), fabsf(__uint_as_float(ua.w)));
                const float4 wb = make_float4(fabsf(__uint_as_float(ub.x)), fabsf(__uint_as_float(ub.y)), fabsf(__uint_as_float(ub.z)), fabsf(__uint_as_float(ub.w)));
                const float ol = (fmaf(wa.x, a0[0], wa.y * a0[1]) + fmaf(wa.z, a1[0], wa.w * a1[1])) + (fmaf(wb.x, a2[0], wb.y * a2[1]) + fmaf(wb.z, a3[0], wb.w * a3[1]));
                const float oh = (fmaf(wa.x, a0[2], wa.y * a0[3]) + fmaf(wa.z, a1[2], wa.w * a1[3])) + (fmaf(wb.x, a2[2], wb.y * a2[3]) + fmaf(wb.z, a3[2], wb.w * a3[3]));
                TWD(6, ol);
                send_word(T3.z, T3.w, pack_bf16(ol, oh), smode2);
                __syncwarp();
                if (l0) mbar_expect(mb + MB_OX * 8, 32);
                TW(7);
            }
#pragma unroll
            for (int s = 4; s < 8; s++) ldsm4t(&S[32 + s * 4], lm_wo + 32768 + s * 2048);
            const uint4 T1 = lds128(tab + 4096);
            {
                mbar_wait(mb + MB_OX * 8, layer);
                TW(8);
                uint4 b[4], ph;
                bool pok;
                ZACC;
                if (layer == 0) {
                    ph = lds128v(sb + OFF_PHI);
                    pok = __all_sync(0xffffffffu, ph.z == 1u);
#pragma unroll
                    for (int i = 0; i < 4; i++) {
                        b[0] = lds128(xb + (OFF_OS - OFF_XS) + i * 64);
                        mbar_wait(mb + (MB_WO0 + i) * 8);
                        ldsm4t(&S[0], lm_wo + i * 4096); ldsm4t(&S[4], lm_wo + i * 4096 + 2048);
                        ldsm4t(&S[8], lm_wo + 32768 + i * 4096); ldsm4t(&S[12], lm_wo + 32768 + i * 4096 + 2048);
                        MMA4(S, 0, 4, 8, 12, b[0], b[0]);
                    }
                    if (w == 0) TS(27);
                } else {
#pragma unroll
                    for (int i = 0; i < 4; i++) b[i] = lds128(xb + (OFF_OS - OFF_XS) + i * 64);
                    __syncwarp();
                    ph = lds128v(sb + OFF_PHI);
                    pok = __all_sync(0xffffffffu, ph.z == 2u);
#pragma unroll
                    for (int i = 0; i < 4; i++) { MMA4(S, i * 8, i * 8 + 4, 32 + i * 8, 32 + i * 8 + 4, b[i], b[i]); }
                }
                if (!pok) {
#pragma unroll 1
                    for (int it = 0; it < (1 << 22); it++) {
                        ph = lds128v(sb + OFF_PHI);
                        if (__all_sync(0xffffffffu, ph.z == (uint32_t)layer + 1)) break;
                    }
                }
                red_pair(mk64(T1.x, T1.y) + layer * 512, fmaf(__uint_as_float(ph.x), PICK4C(0), __uint_as_float(ph.y) * PICK4C(1)), 1);
                bar_arrive(B_RED, 384);
                TW(11);
            }
            if (!ffn) continue;
            const uint32_t w2a = lm + OFF_W2 + wh * 4096;
            const uint4 T2 = lds128(tab + 8192);
            {
                ldsm4t(&S[32], w2a); ldsm4t(&S[36], w2a + 2048); ldsm4t(&S[40], w2a + 8192); ldsm4t(&S[44], w2a + 8192 + 2048);
                mbar_wait(mb + (MB_W130 + wh) * 8);
                if (w == 4 && layer == 0) TS(28);
#pragma unroll
                for (int s = 0; s < 8; s++) ldsm4t(&S[s * 4], T2.w + s * 1024);
                bar_sync(B_X, 384);
                ZACC;
#pragma unroll
                for (int i = 0; i < 2; i++) {
                    const uint4 b = lds128(xb + wh * 256 + i * 128), d = lds128(xb + wh * 256 + i * 128 + 64);
                    MMA4(S, i * 16, i * 16 + 4, i * 16 + 8, i * 16 + 12, b, d);
                }
                const float v0 = (fsel(t2, a0[1], a0[0]) + fsel(t2, a1[1], a1[0])) + (fsel(t2, a2[1], a2[0]) + fsel(t2, a3[1], a3[0]));
                const float v1 = (fsel(t2, a0[3], a0[2]) + fsel(t2, a1[3], a1[2])) + (fsel(t2, a2[3], a2[2]) + fsel(t2, a3[3], a3[2]));
                send_pair(T1.z, T1.w, v0, v1, smode);
                __syncwarp();
                if (l0) mbar_expect(mb + MB_HX * 8, layer ? 64 : 128);
                TW(14);
            }
            if (layer == 0) {
                mbar_wait(mb + MB_W2 * 8);
                if (w == 0) TS(29);
                ldsm4t(&S[32], w2a); ldsm4t(&S[36], w2a + 2048); ldsm4t(&S[40], w2a + 8192); ldsm4t(&S[44], w2a + 8192 + 2048);
            }
            {
                uint16_t xr; asm volatile("ld.shared.u16 %0, [%1];" : "=h"(xr) : "r"(T2.z) : "memory");
                const uint32_t epoch = lds32(sb + OFF_EP);
                bar_sync(B_H, 288);
                const uint4 b = lds128(xb + (OFF_HS - OFF_XS));
                ZACC;
                MMA4(S, 32, 36, 40, 44, b, b);
                const float v = PICK4;
                TWD(16, v);
                if (layer == 0) {
                    red_pair(mk64(T1.x, T1.y) + 128, v, 1);
                    bar_arrive(B_RED, 384);
                    if (w == 0) TS(33);
                } else {
                    float ov, oc;
                    asm volatile("atom.relaxed.gpu.global.add.v2.f32 {%0,%1}, [%2], {%3,%4};" : "=f"(ov), "=f"(oc) : "l"(mk64(T1.x, T1.y) + 640), "f"(v), "f"(1.f) : "memory");
                    if (oc == (float)(kNFFN - 1)) {
                        const float y = __uint_as_float((uint32_t)xr << 16) + bf_lo(pack_bf16(ov + v, 0.f));
                        asm volatile("st.global.u16 [%0], %1;" :: "l"(mk64(T2.x, T2.y)), "h"((uint16_t)pack_bf16(y, 0.f)) : "memory");
                        if (r == 0 && w == 0 && l0) asm volatile("st.relaxed.gpu.global.u32 [%0], %1;" :: "l"(g_epoch_line), "r"(epoch + 1) : "memory");
                    }
                }
            }
        }
    }
}

__device__ __forceinline__ float bfr(float v) { return __bfloat162float(__float2bfloat16(v)); }
__global__ void fb_ln(const __nv_bfloat16* x0, int first) {
    __shared__ float red[2][16];
    const int tid = threadIdx.x;
    float x = first ? __bfloat162float(x0[tid]) : g_fb[tid];
    g_fb[tid] = x;
    float s = x;
    for (int o = 16; o > 0; o >>= 1) s += __shfl_xor_sync(0xffffffffu, s, o);
    if ((tid & 31) == 0) red[0][tid >> 5] = s;
    __syncthreads();
    float m = 0.f;
    for (int i = 0; i < 16; i++) m += red[0][i];
    m *= 1.f / kD;
    float d = (x - m) * (x - m);
    for (int o = 16; o > 0; o >>= 1) d += __shfl_xor_sync(0xffffffffu, d, o);
    if ((tid & 31) == 0) red[1][tid >> 5] = d;
    __syncthreads();
    float v = 0.f;
    for (int i = 0; i < 16; i++) v += red[1][i];
    g_fb[512 + tid] = (x - m) * rsqrtf(v * (1.f / kD) + 1e-5f);
}
__global__ void fb_attn(const __nv_bfloat16* kc, const __nv_bfloat16* vc, const __nv_bfloat16* wq) {
    __shared__ float q[128], s[1024], red[32];
    const int h = blockIdx.x, tid = threadIdx.x;
    if (tid < 128) {
        float a = 0.f;
        for (int d = 0; d < kD; d++) a += g_fb[512 + d] * __bfloat162float(wq[(size_t)d * 4096 + h * 128 + tid]);
        q[tid] = bfr(a);
    }
    __syncthreads();
    const __nv_bfloat16* kr = kc + ((size_t)h * kSK + (kSK - kW) + tid) * kDH;
    float a = 0.f;
    for (int d = 0; d < kDH; d++) a += q[d] * __bfloat162float(kr[d]);
    a *= 0.08838834764831845f;
    float m = a;
    for (int o = 16; o > 0; o >>= 1) m = fmaxf(m, __shfl_xor_sync(0xffffffffu, m, o));
    if ((tid & 31) == 0) red[tid >> 5] = m;
    __syncthreads();
    for (int i = 0; i < 32; i++) m = fmaxf(m, red[i]);
    __syncthreads();
    const float e = expf(a - m);
    s[tid] = e;
    float l = e;
    for (int o = 16; o > 0; o >>= 1) l += __shfl_xor_sync(0xffffffffu, l, o);
    if ((tid & 31) == 0) red[tid >> 5] = l;
    __syncthreads();
    l = 0.f;
    for (int i = 0; i < 32; i++) l += red[i];
    if (tid < 128) {
        float o = 0.f;
        const __nv_bfloat16* vr = vc + ((size_t)h * kSK + (kSK - kW)) * kDH + tid;
        for (int k = 0; k < kW; k++) o += s[k] * __bfloat162float(vr[(size_t)k * kDH]);
        g_fb[1024 + h * 128 + tid] = bfr(o / l);
    }
}
__global__ void fb_up(const __nv_bfloat16* w1, const __nv_bfloat16* w3) {
    const int f = blockIdx.x * blockDim.x + threadIdx.x;
    if (f >= kF) return;
    float a = 0.f, b = 0.f;
    for (int d = 0; d < kD; d++) { a += g_fb[512 + d] * __bfloat162float(w1[(size_t)d * kF + f]); b += g_fb[512 + d] * __bfloat162float(w3[(size_t)d * kF + f]); }
    g_fb[5120 + f] = bfr(a / (1.f + expf(-a)) * b);
}
__global__ void fb_down(const __nv_bfloat16* w, int src, int n, __nv_bfloat16* out) {
    const int col = blockIdx.x * blockDim.x + threadIdx.x;
    float a = 0.f;
    for (int k = 0; k < n; k++) a += g_fb[src + k] * __bfloat162float(w[(size_t)k * kD + col]);
    const float y = bfr(g_fb[col] + bfr(a));
    g_fb[col] = y;
    if (out) out[col] = __float2bfloat16(y);
}

typedef CUresult (*EncodeFn)(CUtensorMap*, CUtensorMapDataType, cuuint32_t, void*, const cuuint64_t*, const cuuint64_t*,
                             const cuuint32_t*, const cuuint32_t*, CUtensorMapInterleave, CUtensorMapSwizzle,
                             CUtensorMapL2promotion, CUtensorMapFloatOOBfill);

bool make_map(EncodeFn fn, CUtensorMap* m, const void* base, uint64_t cols, uint64_t rows, uint32_t bc, uint32_t br, CUtensorMapSwizzle swz) {
    cuuint64_t dims[2] = {cols, rows};
    cuuint64_t strides[1] = {cols * 2};
    cuuint32_t box[2] = {bc, br};
    cuuint32_t es[2] = {1, 1};
    return fn(m, CU_TENSOR_MAP_DATA_TYPE_BFLOAT16, 2, const_cast<void*>(base), dims, strides, box, es, CU_TENSOR_MAP_INTERLEAVE_NONE,
              swz, CU_TENSOR_MAP_L2_PROMOTION_NONE, CU_TENSOR_MAP_FLOAT_OOB_FILL_NONE) == CUDA_SUCCESS;
}

Sched g_sched = {{2150, 2600, 2950, 3200, 3500, 4000, 4700, 5400, 6120, 6430, 6770, 7110, 7700, 8200, 8800, 0},
                 {150, 350, 250, 250, 350, 300, 150, 0}};

}

extern "C" void kernel_launch(void* const* d_in, const int* in_sizes, int n_in, void* d_out, int out_size) {
    (void)in_sizes; (void)n_in; (void)out_size;
    const __nv_bfloat16* x0 = (const __nv_bfloat16*)d_in[0];
    const __nv_bfloat16* kc = (const __nv_bfloat16*)d_in[1];
    const __nv_bfloat16* vc = (const __nv_bfloat16*)d_in[2];
    const __nv_bfloat16* wq = (const __nv_bfloat16*)d_in[3];
    const __nv_bfloat16* wo = (const __nv_bfloat16*)d_in[4];
    const __nv_bfloat16* w1 = (const __nv_bfloat16*)d_in[6];
    const __nv_bfloat16* w3 = (const __nv_bfloat16*)d_in[7];
    const __nv_bfloat16* w2 = (const __nv_bfloat16*)d_in[8];
    __nv_bfloat16* out = (__nv_bfloat16*)d_out;
    cudaStream_t s = cudaStreamPerThread;

    static int state = 0;
    static EncodeFn enc = nullptr;
    if (state == 0) {
        state = 2;
        void* fn = nullptr;
        cudaDriverEntryPointQueryResult qr;
        if (cudaGetDriverEntryPoint("cuTensorMapEncodeTiled", &fn, cudaEnableDefault, &qr) == cudaSuccess && fn &&
            cudaFuncSetAttribute(fused_kernel, cudaFuncAttributeMaxDynamicSharedMemorySize, SMEM_BYTES) == cudaSuccess) {
            enc = (EncodeFn)fn;
            cudaLaunchConfig_t cfg = {};
            cfg.gridDim = dim3(kNCTA); cfg.blockDim = dim3(kNTHR); cfg.dynamicSmemBytes = SMEM_BYTES;
            cudaLaunchAttribute at[1];
            at[0].id = cudaLaunchAttributeClusterDimension;
            at[0].val.clusterDim.x = 2; at[0].val.clusterDim.y = 1; at[0].val.clusterDim.z = 1;
            cfg.attrs = at; cfg.numAttrs = 1;
            int ncl = 0;
            if (cudaOccupancyMaxActiveClusters(&ncl, fused_kernel, &cfg) == cudaSuccess && ncl >= kNCTA / 2) state = 1;
        }
        (void)cudaGetLastError();
    }
    if (state == 1) {
        Maps tm;
        bool ok = make_map(enc, &tm.m[0], wq, 4096, 512, 64, 64, CU_TENSOR_MAP_SWIZZLE_128B) &&
                  make_map(enc, &tm.m[1], vc, 128, (uint64_t)kHQ * kSK, 64, 64, CU_TENSOR_MAP_SWIZZLE_128B) &&
                  make_map(enc, &tm.m[2], wo, 512, 4096, 64, 32, CU_TENSOR_MAP_SWIZZLE_128B) &&
                  make_map(enc, &tm.m[3], w1, kF, 512, 32, 128, CU_TENSOR_MAP_SWIZZLE_64B) &&
                  make_map(enc, &tm.m[4], w3, kF, 512, 32, 128, CU_TENSOR_MAP_SWIZZLE_64B) &&
                  make_map(enc, &tm.m[5], w2, 512, kF, 64, 32, CU_TENSOR_MAP_SWIZZLE_128B);
        if (ok) {
            fused_kernel<<<kNCTA, kNTHR, SMEM_BYTES, s>>>(kc, x0, out, g_sched, tm);
            return;
        }
    }
    for (int layer = 0; layer < 2; layer++) {
        fb_ln<<<1, 512, 0, s>>>(x0, layer == 0);
        fb_attn<<<kHQ, 1024, 0, s>>>(kc, vc, wq);
        fb_down<<<8, 64, 0, s>>>(wo, 1024, 4096, nullptr);
        fb_ln<<<1, 512, 0, s>>>(x0, 0);
        fb_up<<<(kF + 63) / 64, 64, 0, s>>>(w1, w3);
        fb_down<<<8, 64, 0, s>>>(w2, 5120, kF, layer == 1 ? out : nullptr);
    }
}
```

```cpp
#include <cuda_runtime.h>
#include <cuda_bf16.h>
#include <cuda.h>
#include <stdint.h>

namespace {

constexpr int kD = 512, kHQ = 32, kDH = 128, kSK = 4096, kW = 1024, kF = 1376;
constexpr int kNCTA = 128, kNTHR = 384;
constexpr int kNFFN = 43;

struct Sched {
    int t[16];
    int dar[8];
};

struct Maps { CUtensorMap m[6]; };

constexpr uint32_t OFF_WQ = 0;
constexpr uint32_t OFF_WO = 65536;
constexpr uint32_t OFF_W2 = 131072;
constexpr uint32_t OFF_W1 = 147456;
constexpr uint32_t OFF_W3 = 163840;
constexpr uint32_t OFF_V = OFF_W2;
constexpr uint32_t OFF_XS = 196608;
constexpr uint32_t OFF_ONE = OFF_XS + 576;
constexpr uint32_t OFF_XF = OFF_XS + 1152;
constexpr uint32_t OFF_HP = OFF_XF + 512;
constexpr uint32_t OFF_QP = OFF_HP + 2048;
constexpr uint32_t OFF_QS = OFF_QP + 2048;
constexpr uint32_t OFF_OS = OFF_QS + 256;
constexpr uint32_t OFF_PS = OFF_QS + 1152;
constexpr uint32_t OFF_MS = OFF_PS + 1152;
constexpr uint32_t OFF_HS = OFF_QS + 512;
constexpr uint32_t OFF_RS = OFF_MS + 64;
constexpr uint32_t OFF_PHI = OFF_RS + 32;
constexpr uint32_t OFF_EP = OFF_PHI + 16;
constexpr uint32_t OFF_DL = OFF_EP + 16;
constexpr uint32_t OFF_MB = OFF_DL + 16;
constexpr uint32_t OFF_TAB = OFF_MB + 256;
constexpr uint32_t SMEM_USED = OFF_TAB + 16384;
constexpr uint32_t SMEM_BYTES = SMEM_USED + 1024;
enum { MB_K = 0, MB_KFREE, MB_VFREE, MB_WQ, MB_V0  , MB_WO0 = MB_V0 + 4  , MB_W130 = MB_WO0 + 4  , MB_W2 = MB_W130 + 2,
       MB_QX, MB_HX, MB_OX, MB_COUNT };
static_assert(OFF_W3 == OFF_W1 + 16384 && OFF_QP == OFF_HP + 2048 && SMEM_BYTES <= 232448, "layout");
enum { B_X = 1, B_S, B_H, B_RED, B_Q, B_ST };

__device__ __align__(256) float g_ar_raw[8192 + 8192];
__device__ __align__(256) unsigned g_epoch_line[64];
__device__ __align__(256) unsigned g_flag_line[64];
__device__ float g_fb[8192];

__device__ __forceinline__ uint32_t smem_u32(const void* p) { return (uint32_t)__cvta_generic_to_shared(p); }
__device__ __forceinline__ void mbar_init(uint32_t bar, int cnt) { asm volatile("mbarrier.init.shared::cta.b64 [%0], %1;" :: "r"(bar), "r"(cnt) : "memory"); }
__device__ __forceinline__ void mbar_expect(uint32_t bar, uint32_t bytes) { asm volatile("mbarrier.arrive.expect_tx.shared::cta.b64 _, [%0], %1;" :: "r"(bar), "r"(bytes) : "memory"); }
__device__ __forceinline__ void mbar_arrive(uint32_t bar) { asm volatile("mbarrier.arrive.shared::cta.b64 _, [%0];" :: "r"(bar) : "memory"); }
__device__ __forceinline__ void mbar_wait(uint32_t bar, uint32_t ph = 0) {
    for (int i = 0; i < (1 << 20); i++) {
        uint32_t ok;
        asm volatile("{\n.reg .pred p;\nmbarrier.try_wait.parity.shared::cta.b64 p, [%1], %2;\nselp.u32 %0, 1, 0, p;\n}" : "=r"(ok) : "r"(bar), "r"(ph) : "memory");
        if (ok) break;
    }
}
__device__ __forceinline__ void bar_sync(int id, int n) { asm volatile("bar.sync %0, %1;" :: "r"(id), "r"(n) : "memory"); }
__device__ __forceinline__ void bar_arrive(int id, int n) { asm volatile("bar.arrive %0, %1;" :: "r"(id), "r"(n) : "memory"); }
__device__ __forceinline__ void tma2d(uint32_t dst, const CUtensorMap* tm, int c0, int c1, uint32_t bar) {
    asm volatile("cp.async.bulk.tensor.2d.shared::cluster.global.mbarrier::complete_tx::bytes [%0], [%1, {%3, %4}], [%2];"
                 :: "r"(dst), "l"((uint64_t)tm), "r"(bar), "r"(c0), "r"(c1) : "memory");
}
__device__ __forceinline__ void ldsm4t(uint32_t* r, uint32_t addr) {
    asm volatile("ldmatrix.sync.aligned.m8n8.x4.trans.shared.b16 {%0,%1,%2,%3}, [%4];" : "=r"(r[0]), "=r"(r[1]), "=r"(r[2]), "=r"(r[3]) : "r"(addr) : "memory");
}
__device__ __forceinline__ void mma16(float* c, uint32_t a0, uint32_t a1, uint32_t a2, uint32_t a3, uint32_t b0, uint32_t b1) {
    asm volatile("mma.sync.aligned.m16n8k16.row.col.f32.bf16.bf16.f32 {%0,%1,%2,%3}, {%4,%5,%6,%7}, {%8,%9}, {%0,%1,%2,%3};"
                 : "+f"(c[0]), "+f"(c[1]), "+f"(c[2]), "+f"(c[3]) : "r"(a0), "r"(a1), "r"(a2), "r"(a3), "r"(b0), "r"(b1));
}
__device__ __forceinline__ uint4 lds128(uint32_t a) { uint4 v; asm volatile("ld.shared.v4.u32 {%0,%1,%2,%3}, [%4];" : "=r"(v.x), "=r"(v.y), "=r"(v.z), "=r"(v.w) : "r"(a) : "memory"); return v; }
__device__ __forceinline__ float4 lds128f(uint32_t a) { float4 v; asm volatile("ld.shared.v4.f32 {%0,%1,%2,%3}, [%4];" : "=f"(v.x), "=f"(v.y), "=f"(v.z), "=f"(v.w) : "r"(a) : "memory"); return v; }
__device__ __forceinline__ void sts16(uint32_t a, uint32_t v) { asm volatile("st.shared.u16 [%0], %1;" :: "r"(a), "h"((uint16_t)v) : "memory"); }
__device__ __forceinline__ void sts32(uint32_t a, uint32_t v) { asm volatile("st.shared.u32 [%0], %1;" :: "r"(a), "r"(v) : "memory"); }
__device__ __forceinline__ void send_pair(uint32_t a, uint32_t rbar, float v0, float v1, uint32_t mode) {
    asm volatile("{\n.reg .pred pl, pr;\nsetp.eq.u32 pl, %4, 1;\nsetp.eq.u32 pr, %4, 2;\n"
                 "@pr st.async.shared::cluster.mbarrier::complete_tx::bytes.v2.f32 [%0], {%1,%2}, [%3];\n"
                 "@pl st.shared.v2.f32 [%0], {%1,%2};\n}" :: "r"(a), "f"(v0), "f"(v1), "r"(rbar), "r"(mode) : "memory");
}
__device__ __forceinline__ void send_word(uint32_t a, uint32_t rbar, uint32_t v, uint32_t mode) {
    asm volatile("{\n.reg .pred pl, pr;\nsetp.eq.u32 pl, %3, 1;\nsetp.eq.u32 pr, %3, 2;\n"
                 "@pr st.async.shared::cluster.mbarrier::complete_tx::bytes.b32 [%0], %1, [%2];\n"
                 "@pl st.shared.b32 [%0], %1;\n}" :: "r"(a), "r"(v), "r"(rbar), "r"(mode) : "memory");
}
__device__ __forceinline__ void red_pair(const void* p, float v, uint32_t on) {
    asm volatile("{\n.reg .pred p;\nsetp.ne.u32 p, %3, 0;\n@p red.relaxed.gpu.global.add.v2.f32 [%0], {%1,%2};\n}" :: "l"(p), "f"(v), "f"(1.f), "r"(on) : "memory");
}
__device__ __forceinline__ float fsel(bool p, float a, float b) { float r; asm("{\n.reg .pred q;\nsetp.ne.u32 q, %3, 0;\nselp.f32 %0, %1, %2, q;\n}" : "=f"(r) : "f"(a), "f"(b), "r"((uint32_t)p)); return r; }
__device__ __forceinline__ void sts128(uint32_t a, uint32_t x, uint32_t y, uint32_t z, uint32_t w) { asm volatile("st.shared.v4.u32 [%0], {%1,%2,%3,%4};" :: "r"(a), "r"(x), "r"(y), "r"(z), "r"(w) : "memory"); }
__device__ __forceinline__ uint2 lds64(uint32_t a) { uint2 v; asm volatile("ld.shared.v2.u32 {%0,%1}, [%2];" : "=r"(v.x), "=r"(v.y) : "r"(a) : "memory"); return v; }
__device__ __forceinline__ uint4 lds128v(uint32_t a) { uint4 v; asm volatile("ld.volatile.shared.v4.u32 {%0,%1,%2,%3}, [%4];" : "=r"(v.x), "=r"(v.y), "=r"(v.z), "=r"(v.w) : "r"(a) : "memory"); return v; }
__device__ __forceinline__ uint32_t lds32(uint32_t a) { uint32_t v; asm volatile("ld.shared.u32 %0, [%1];" : "=r"(v) : "r"(a) : "memory"); return v; }
__device__ __forceinline__ float rsq(float x) { float r; asm("rsqrt.approx.ftz.f32 %0, %1;" : "=f"(r) : "f"(x)); return r; }
__device__ __forceinline__ float rcp(float x) { float r; asm("rcp.approx.ftz.f32 %0, %1;" : "=f"(r) : "f"(x)); return r; }
__device__ __forceinline__ const char* mk64(uint32_t lo, uint32_t hi) { return (const char*)(((uint64_t)hi << 32) | lo); }
__device__ __forceinline__ unsigned gtime() { unsigned t; asm volatile("mov.u32 %0, %%globaltimer_lo;" : "=r"(t)); return t; }
__device__ __forceinline__ unsigned clk() { unsigned t; asm volatile("mov.u32 %0, %%clock;" : "=r"(t)); return t; }
__device__ __forceinline__ void spin(int n) { const unsigned t = clk(); while ((int)(clk() - t) < n) {} }
__device__ __forceinline__ void pace(unsigned t0, int ns) { for (int i = 0; i < (1 << 16) && (int)(gtime() - t0) < ns; i++) {} }
__device__ __forceinline__ uint4 ld_poll(const void* p) {
    unsigned long long a, b;
    asm volatile("ld.relaxed.gpu.global.v2.b64 {%0,%1}, [%2];" : "=l"(a), "=l"(b) : "l"(p) : "memory");
    return make_uint4((uint32_t)a, (uint32_t)(a >> 32), (uint32_t)b, (uint32_t)(b >> 32));
}
__device__ __forceinline__ void st_pkt(const void* p, uint32_t v, uint32_t tag, uint32_t on) {
    asm volatile("{\n.reg .pred p;\n.reg .b64 d;\nsetp.ne.u32 p, %3, 0;\nmov.b64 d, {%1,%2};\n@p st.relaxed.gpu.global.b64 [%0], d;\n}" :: "l"(p), "r"(v), "r"(tag), "r"(on) : "memory");
}
__device__ __forceinline__ uint32_t pack_bf16(float lo, float hi) {
    uint32_t r; asm("cvt.rn.bf16x2.f32 %0, %1, %2;" : "=r"(r) : "f"(hi), "f"(lo)); return r;
}
__device__ __forceinline__ float bf_lo(uint32_t v) { return __uint_as_float(v << 16); }
__device__ __forceinline__ float bf_hi(uint32_t v) { return __uint_as_float(v & 0xffff0000u); }
__device__ __forceinline__ float ex2(float x) { float r; asm("ex2.approx.ftz.f32 %0, %1;" : "=f"(r) : "f"(x)); return r; }
__device__ __forceinline__ float warp_max(float v) {
    int i = __float_as_int(v);
    i ^= (i >> 31) & 0x7fffffff;
    i = __reduce_max_sync(0xffffffffu, i);
    i ^= (i >> 31) & 0x7fffffff;
    return __int_as_float(i);
}
__device__ __forceinline__ uint32_t ar_off(int k, int ln) {
    return (ln >> 1) * 1024 + (ln & 1) * 256 + (k & 1) * 128 + (k >> 1) * 512;
}

#define MMA4(A, i0, i1, i2, i3, b, d) \
    mma16(a0, A[i0], A[i0 + 1], A[i0 + 2], A[i0 + 3], b.x, b.y); \
    mma16(a1, A[i1], A[i1 + 1], A[i1 + 2], A[i1 + 3], b.z, b.w); \
    mma16(a2, A[i2], A[i2 + 1], A[i2 + 2], A[i2 + 3], d.x, d.y); \
    mma16(a3, A[i3], A[i3 + 1], A[i3 + 2], A[i3 + 3], d.z, d.w);
#define STAGE_WO(lo, hi) _Pragma("unroll") for (int f_ = lo; f_ < hi; f_++) ldsm4t(&S[(f_ & 1) * 32 + (f_ >> 1) * 4], lm_wo + (f_ & 1) * 32768 + (f_ >> 1) * 2048)
#define ZACC float a0[4] = {0.f, 0.f, 0.f, 0.f}, a1[4] = {0.f, 0.f, 0.f, 0.f}, a2[4] = {0.f, 0.f, 0.f, 0.f}, a3[4] = {0.f, 0.f, 0.f, 0.f}
#define LN_STATS \
    const float4 r0_ = lds128f(sb + OFF_RS), r1_ = lds128f(sb + OFF_RS + 16); \
    const float mean_ = ((r0_.x + r0_.z) + (r1_.x + r1_.z)) * (1.f / kD); \
    const float rstd = rsq(fmaxf(fmaf(-mean_, mean_, fmaf((r0_.y + r0_.w) + (r1_.y + r1_.w), 1.f / kD, 1e-5f)), 1e-5f)); \
    const float nmr = -mean_ * rstd
#define PICK4C(k) (fsel(t2, fsel(t1, a2[2 + k], a2[k]), fsel(t1, a0[2 + k], a0[k])) + fsel(t2, fsel(t1, a3[2 + k], a3[k]), fsel(t1, a1[2 + k], a1[k])))
#define PICK4 (fsel(t2, fsel(t1, a2[2], a2[0]), fsel(t1, a0[2], a0[0])) + fsel(t2, fsel(t1, a3[2], a3[0]), fsel(t1, a1[2], a1[0])))

__global__ void __cluster_dims__(2, 1, 1) __launch_bounds__(kNTHR, 1)
fused_kernel(const __nv_bfloat16* __restrict__ kc, const __nv_bfloat16* __restrict__ x0, __nv_bfloat16* __restrict__ out,
             const __grid_constant__ Sched sc, const __grid_constant__ Maps tm) {
    extern __shared__ uint8_t smem_raw[];
    const uint32_t sb = (smem_u32(smem_raw) + 1023u) & ~1023u;
    const uint32_t mb = sb + OFF_MB;
    const int tid = threadIdx.x;
    const int c = blockIdx.x;
    asm volatile("{\n.reg .pred p;\nsetp.eq.u32 p, %0, 352;\n"
                 "@p mbarrier.init.shared::cta.b64 [%1], 1;\n"
                 "@p fence.mbarrier_init.release.cluster;\n"
                 "@p mbarrier.arrive.expect_tx.shared::cta.b64 _, [%1], 65536;\n"
                 "@p cp.async.bulk.shared::cluster.global.mbarrier::complete_tx::bytes [%2], [%3], 65536, [%1];\n}"
                 :: "r"(tid), "r"(mb + MB_K * 8), "r"(sb + OFF_WO),
                    "l"((const char*)kc + ((size_t)(c >> 2) << 20) + (size_t)((kSK - kW) * kDH * 2 + (c & 3) * 65536)) : "memory");
    const unsigned t0 = gtime();
    const int warp = __shfl_sync(0xffffffffu, tid >> 5, 0), lane = tid & 31;
    const int h = c >> 2, j = c & 3, r = c & 1, p = c >> 1;
    const int g = lane >> 2, t = lane & 3;
    const bool ffn = p < kNFFN;
    char* const ar = (char*)(((uintptr_t)g_ar_raw + 32767) & ~(uintptr_t)32767);
    uint32_t rsb;
    asm("mapa.shared::cluster.u32 %0, %1, %2;" : "=r"(rsb) : "r"(sb), "r"(r ^ 1));

    if (warp >= 8) {
        asm volatile("setmaxnreg.dec.sync.aligned.u32 40;");
        const int cw = warp - 8;
        if (cw == 3) {
            if (lane >= 1 && lane < MB_COUNT) {
                const bool tma = lane >= MB_WQ && lane <= MB_W2;
                mbar_init(mb + lane * 8, tma ? 1 : lane == MB_OX ? 9 : 8);
                if (tma) mbar_expect(mb + lane * 8, lane == MB_WQ ? 65536 : 16384);
            }
            asm volatile("fence.mbarrier_init.release.cluster;" ::: "memory");
            __syncwarp();
        } else if (cw == 2 && lane < 6) {
            asm volatile("prefetch.tensormap [%0];" :: "l"((uint64_t)&tm.m[lane]) : "memory");
        }
        __syncwarp();
        asm volatile("barrier.cluster.arrive.relaxed.aligned;" ::: "memory");
        uint32_t xp = *(const uint32_t*)(x0 + r * 256 + cw * 64 + lane * 2);
        uint32_t xq = *(const uint32_t*)(x0 + (r ^ 1) * 256 + cw * 64 + lane * 2);
        sts32(sb + OFF_ONE + cw * 128 + lane * 4, 0x3F803F80u);
        if (lane < 4) sts32(sb + OFF_DL + lane * 4, sc.dar[ffn || lane == 0 ? lane : lane + 4]);
        const int dos2 = sc.dar[4];
        __syncwarp();
        const uint32_t xs_a = __shfl_sync(0xffffffffu, sb + OFF_XS + cw * 128 + ((lane >> 4) & 1) * 64 + (lane & 3) * 16 + ((lane >> 3) & 1) * 8 + ((lane >> 2) & 1) * 4, lane);
        const uint32_t xf_a = __shfl_sync(0xffffffffu, sb + OFF_XF + cw * 128 + lane * 4, lane);
        const uint32_t ar_o = __shfl_sync(0xffffffffu, ar_off(0, r * 16 + cw * 4 + (lane >> 3)) + (lane & 7) * 16, lane);

        auto xstage = [&](int st) -> bool {
            const uint32_t tg = __float_as_uint((st & 1) ? 64.f : (float)kNFFN);
            const bool act = ffn || !(st & 1);
            const char* a = ar + (ar_o + ((st - 1) & 1) * 128 + ((st - 1) >> 1) * 512);
            const char* a2 = (const char*)((uintptr_t)a ^ 8192);
            uint4 u = make_uint4(0, tg, 0, tg);
            if (st > 0) {
                const int dar = lds32(sb + OFF_DL + st * 4);
                if (ffn || (st & 1)) bar_sync(B_RED, 384);
                if (!ffn) {
                    if (st == 3) return false;
                    if (st == 2) {
                        const unsigned want = lds32(sb + OFF_EP) + 1;
#pragma unroll 1
                        for (int it = 0; it < (1 << 18); it++) {
                            unsigned fl;
                            asm volatile("ld.relaxed.gpu.global.u32 %0, [%1];" : "=r"(fl) : "l"(ar + 24576 + (c - 2 * kNFFN) * 128) : "memory");
                            if (__all_sync(0xffffffffu, fl == want)) break;
                        }
                    }
                }
                spin(dar);
                uint4 v;
#pragma unroll 1
                for (int it = 0; it < (1 << 18); it++) {
                    v = ld_poll(a);
                    u = ld_poll(a2);
                    if (__all_sync(0xffffffffu, v.y == tg && v.w == tg)) break;
                }
                const uint32_t d = pack_bf16(__uint_as_float(v.x), __uint_as_float(v.z));
                xp = pack_bf16(bf_lo(xp) + bf_lo(d), bf_hi(xp) + bf_hi(d));
            }
            if (act) {
                sts32(xs_a, xp);
                sts32(xf_a, xp);
                bar_arrive(B_X, 384);
            }
#pragma unroll 1
            for (int it = 0; it < (1 << 18); it++) {
                if (__all_sync(0xffffffffu, u.y == tg && u.w == tg)) break;
                u = ld_poll(a2);
            }
            const uint32_t d = pack_bf16(__uint_as_float(u.x), __uint_as_float(u.z));
            xq = pack_bf16(bf_lo(xq) + bf_lo(d), bf_hi(xq) + bf_hi(d));
            if (!act) return false;
            const float xa = bf_lo(xp), xb = bf_hi(xp), xc = bf_lo(xq), xd = bf_hi(xq);
            float s1 = (xa + xb) + (xc + xd), s2 = fmaf(xa, xa, xb * xb) + fmaf(xc, xc, xd * xd);
            {
                const uint32_t e = __reduce_max_sync(0xffffffffu, __float_as_uint(fmaxf(fmaxf(fabsf(xa), fabsf(xb)), fmaxf(fabsf(xc), fabsf(xd)))) >> 23);
                const uint32_t ec = min(max(e, 70u), 185u);
                const float inv = __uint_as_float((253u - ec) << 23), up = __uint_as_float((ec + 1u) << 23);
                const int i1 = __reduce_add_sync(0xffffffffu, __float2int_rn(s1 * inv * 4194304.f));
                const int i2 = __reduce_add_sync(0xffffffffu, __float2int_rn(s2 * inv * inv * 4194304.f));
                if (e > 185u) {
#pragma unroll
                    for (int o = 16; o > 0; o >>= 1) { s1 += __shfl_xor_sync(0xffffffffu, s1, o); s2 += __shfl_xor_sync(0xffffffffu, s2, o); }
                } else {
                    s1 = __int2float_rn(i1) * (up * (1.f / 4194304.f));
                    s2 = __int2float_rn(i2) * (up * up * (1.f / 4194304.f));
                }
            }
            asm volatile("st.shared.v2.f32 [%0], {%1,%2};" :: "r"(sb + OFF_RS + cw * 8), "f"(s1), "f"(s2) : "memory");
            if (cw == 0) bar_sync(B_ST, 128); else bar_arrive(B_ST, 128);
            return true;
        };
        auto phi_stage = [&](const char* sp, uint32_t tag, int layer) {
            uint4 e0, e1, e2, e3;
#pragma unroll 1
            for (int it = 0; it < (1 << 18); it++) {
                e0 = ld_poll(sp); e1 = ld_poll(sp + 32); e2 = ld_poll(sp + 64); e3 = ld_poll(sp + 96);
                if (__all_sync(0xffffffffu, e0.y == tag && e0.w == tag && e1.y == tag && e1.w == tag && e2.y == tag && e2.w == tag && e3.y == tag && e3.w == tag)) break;
                if (__any_sync(0xffffffffu, lds128v(sb + OFF_PHI).z == (uint32_t)layer + 1)) return;
            }
            const float Mh = fmaxf(fmaxf(__uint_as_float(e0.x), __uint_as_float(e1.x)), fmaxf(__uint_as_float(e2.x), __uint_as_float(e3.x)));
            const float w0 = ex2(__uint_as_float(e0.x) - Mh), w1 = ex2(__uint_as_float(e1.x) - Mh), w2 = ex2(__uint_as_float(e2.x) - Mh), w3 = ex2(__uint_as_float(e3.x) - Mh);
            const float il = rcp(fmaf(w0, __uint_as_float(e0.z), w1 * __uint_as_float(e1.z)) + fmaf(w2, __uint_as_float(e2.z), w3 * __uint_as_float(e3.z)));
            sts128(sb + OFF_PHI, __float_as_uint(((j & 2) ? w2 : w0) * il), __float_as_uint(((j & 2) ? w3 : w1) * il), layer + 1, 0);
        };

        if (cw == 0) {
            asm volatile("barrier.cluster.wait.acquire.aligned;" ::: "memory");
            const uint32_t l16 = __shfl_sync(0xffffffffu, sb + OFF_HP + lane * 16, lane);
            const uint32_t qs_a = __shfl_sync(0xffffffffu, sb + OFF_QS + g * 32 + t * 4, lane);
            const uint32_t hs_a = __shfl_sync(0xffffffffu, sb + OFF_HS + ((lane & 7) >> 1) * 16 + (lane >> 4) * 8 + ((lane >> 3) & 1) * 4 + (lane & 1) * 2, lane);
            float cs[4] = {0.f, 0.f, 0.f, 0.f}, c1 = 0.f, c3 = 0.f;
#pragma unroll 1
            for (int st = 0; st < 4; st++) {
                if (!xstage(st)) continue;
                LN_STATS;
                if (!(st & 1)) {
                    mbar_wait(mb + MB_QX * 8, st >> 1);
                    const float4 a = lds128f(l16 + 2048), b = lds128f(l16 + 2048 + 512);
                    if (st == 0) {
                        const float4 u = lds128f(l16 + 2048 + 1024), w = lds128f(l16 + 2048 + 1536);
                        cs[0] = u.x + w.x; cs[1] = u.y + w.y; cs[2] = u.z + w.z; cs[3] = u.w + w.w;
                    }
                    const float q0 = fmaf(rstd, a.x + b.x, nmr * cs[0]), q8 = fmaf(rstd, a.y + b.y, nmr * cs[1]);
                    const float q1 = fmaf(rstd, a.z + b.z, nmr * cs[2]), q9 = fmaf(rstd, a.w + b.w, nmr * cs[3]);
                    const uint32_t qa = pack_bf16(q0, q1), qb = pack_bf16(q8, q9);
                    sts32(qs_a, qa); sts32(qs_a + 16, qb);
                    bar_arrive(B_Q, 288);
                    if (st == 0) {
                        const unsigned want = lds32(sb + OFF_EP) + 1;
#pragma unroll 1
                        for (int it = 0; it < (1 << 18); it++) {
                            unsigned fl;
                            asm volatile("ld.acquire.gpu.global.u32 %0, [%1];" : "=r"(fl) : "l"(g_flag_line + (lane & 15)) : "memory");
                            if (__all_sync(0xffffffffu, fl == want)) break;
                        }
                    }
                    if (lane == 0) mbar_arrive(mb + MB_OX * 8);
                    __syncwarp();
                } else {
                    mbar_wait(mb + MB_HX * 8, st >> 1);
                    const float4 a = lds128f(l16), b = lds128f(l16 + 512);
                    if (st == 1) {
                        const float4 u = lds128f(l16 + 1024), w = lds128f(l16 + 1536);
                        c1 = (u.x + u.z) + (w.x + w.z); c3 = (u.y + u.w) + (w.y + w.w);
                    }
                    const float gate = fmaf(rstd, (a.x + a.z) + (b.x + b.z), nmr * c1), up = fmaf(rstd, (a.y + a.w) + (b.y + b.w), nmr * c3);
                    const float hv = gate * up * rcp(1.f + ex2(-1.4426950408889634f * gate));
                    const uint32_t hb = pack_bf16(hv, 0.f);
                    sts16(hs_a, hb); sts16(hs_a + 576, hb);
                    bar_arrive(B_H, 288);
                }
            }
        } else if (cw == 1) {
            unsigned epoch;
            asm volatile("ld.relaxed.gpu.global.u32 %0, [%1];" : "=r"(epoch) : "l"(g_epoch_line) : "memory");
            const char* const my_st = ar + 16384 + c * 32 + t * 8 + (g & 1) * 4096;
            st_pkt(my_st, 0, 0, lane < 8);
            sts32(sb + OFF_MS + 32 + g * 4, 0x80000000u);
            if (lane == 0) { sts128(sb + OFF_PHI, 0, 0, 0, 0); sts32(sb + OFF_EP, epoch); }
            asm volatile("barrier.cluster.wait.acquire.aligned;" ::: "memory");
#pragma unroll 1
            for (int st = 0; st < 4; st++) {
                if (!xstage(st) || (st & 1)) continue;
                const uint32_t tag = epoch * 2 + (st >> 1) + 1;
                bar_sync(B_S, 320);
                const uint4 pv = lds128(sb + OFF_PS + lane * 16);
                const float4 m0 = lds128f(sb + OFF_MS), m1 = lds128f(sb + OFF_MS + 16);
                const float mg = __uint_as_float(lds32(sb + OFF_MS + g * 4));
                const float M = fmaxf(fmaxf(fmaxf(m0.x, m0.y), fmaxf(m0.z, m0.w)), fmaxf(fmaxf(m1.x, m1.y), fmaxf(m1.z, m1.w)));
                const float al = ex2(mg - M);
                sts32(sb + OFF_MS + 32 + g * 4, (__float_as_uint(al) & 0x7fffffffu) | ((uint32_t)st << 30));
                const float lp = (((bf_lo(pv.x) + bf_hi(pv.x)) + (bf_lo(pv.y) + bf_hi(pv.y))) + ((bf_lo(pv.z) + bf_hi(pv.z)) + (bf_lo(pv.w) + bf_hi(pv.w)))) * (al * 8388608.f);
                const float L = __uint2float_rn(__reduce_add_sync(0xffffffffu, __float2uint_rn(lp))) * (1.f / 8388608.f);
                st_pkt(my_st, __float_as_uint((lane & 1) ? L : M), tag, lane < 8);
                spin(lds32(sb + OFF_DL));
                phi_stage(ar + 16384 + h * 128, tag, st >> 1);
            }
        } else if (cw == 2) {
            unsigned epoch;
            asm volatile("ld.relaxed.gpu.global.u32 %0, [%1];" : "=r"(epoch) : "l"(g_epoch_line) : "memory");
            st_pkt(ar + 24576 + c * 128 + lane * 8, 0, 0, lane < 4 && c < kNCTA - 2 * kNFFN);
            if (c < 16) {
                asm volatile("st.relaxed.gpu.global.v4.u32 [%0], {%1,%1,%1,%1};" :: "l"(ar + c * 1024 + lane * 16), "r"(0) : "memory");
                asm volatile("st.relaxed.gpu.global.v4.u32 [%0], {%1,%1,%1,%1};" :: "l"(ar + c * 1024 + 512 + lane * 16), "r"(0) : "memory");
                __threadfence();
                __syncwarp();
                if (lane == 0) asm volatile("st.relaxed.gpu.global.u32 [%0], %1;" :: "l"(g_flag_line + c), "r"(epoch + 1) : "memory");
            }
            asm volatile("barrier.cluster.wait.acquire.aligned;" ::: "memory");
#pragma unroll 1
            for (int st = 0; st < 4; st++) {
                if (!xstage(st)) continue;
                if (st & 1) {
                    if (st == 1 && c < kNCTA - 2 * kNFFN) {
                        mbar_wait(mb + MB_W2 * 8);
                        mbar_wait(mb + MB_HX * 8);
                        st_pkt(ar + 24576 + c * 128 + lane * 8, epoch + 1, 0, lane < 4);
                    }
                    continue;
                }
                bar_sync(B_S, 320);
                spin(dos2);
                phi_stage(ar + 16384 + 4096 + h * 128, epoch * 2 + (st >> 1) + 1, st >> 1);
            }
        } else {
            const int ty = lane >> 2, q = lane & 3;
            const bool w13 = ty == 3 && q < 2;
            const uint32_t c_dst = sb + (ty == 0 ? OFF_WQ + q * 8192 : ty == 1 ? OFF_V + q * 16384 : ty == 2 ? OFF_WO + q * 4096 : w13 ? OFF_W1 + q * 8192 : OFF_W2);
            const uint32_t c_dd = ty == 0 ? 32768 : ty == 1 ? 8192 : ty == 2 || w13 ? 16384 : 4096;
            const int c_x = ty == 0 ? h * 128 : ty == 1 ? 0 : w13 ? p * 32 : r * 256;
            const int c_y = ty == 0 ? r * 256 + q * 64 : ty == 1 ? h * kSK + (kSK - kW) + j * 256 + q * 64 : ty == 2 ? h * 128 + q * 32 : w13 ? r * 256 + q * 128 : p * 32;
            const uint32_t c_inf = (uint32_t)sc.t[lane & 15] | ((ty < 3 || w13 ? ty : 5) << 16) | ((ty < 2 || w13 ? 2 : 4) << 20) | (w13 ? 1u << 24 : 0u);
            const int nch = ffn ? 15 : 12;
#pragma unroll 1
            for (int i = 0; i < nch; i++) {
                const uint32_t dst = __shfl_sync(0xffffffffu, c_dst, i), dd = __shfl_sync(0xffffffffu, c_dd, i), inf = __shfl_sync(0xffffffffu, c_inf, i);
                const int x = __shfl_sync(0xffffffffu, c_x, i), y = __shfl_sync(0xffffffffu, c_y, i);
                if (i == 5) {
                    asm volatile("barrier.cluster.wait.acquire.aligned;" : "+r"(xp), "+r"(xq) :: "memory");
                    xstage(0);
                }
                if (i >= 8) mbar_wait(mb + (i < 12 ? MB_KFREE : MB_VFREE) * 8);
                pace(t0, inf & 0xffff);
                if (lane < (int)((inf >> 20) & 7))
                    tma2d(dst + lane * dd, &tm.m[((inf >> 16) & 7) + (inf >> 24) * lane], x + ((inf >> 24) ? 0 : lane * 64), y, mb + (MB_WQ + max(i - 3, 0)) * 8);
                __syncwarp();
            }
#pragma unroll 1
            for (int st = 1; st < 4; st++) xstage(st);
        }
    } else {
        asm volatile("setmaxnreg.inc.sync.aligned.u32 232;");
        asm volatile("barrier.cluster.arrive.relaxed.aligned;" ::: "memory");
        const int w = warp;
        const bool t1 = t & 1, t2 = t & 2, l0 = lane == 0;
        uint32_t KR[64], VR[64], S[64];
        {
            const int mt = w & 3, kh = w >> 2, ln = w + 8 * (t >> 1), cc = g + 8 * (t & 1);
            const uint32_t snd = ((t & 1) ? rsb : sb) + r * 512 + (t >> 1) * 1024;
            const uint64_t arc = (uint64_t)(ar + ar_off(0, r * 16 + ln) + cc * 8), op = (uint64_t)(out + r * 256 + ln * 16 + cc);
            const uint32_t sn2 = ((t & 1) ? rsb : sb) + r * 576;
            sts128(sb + OFF_TAB + tid * 16, snd + OFF_QP + w * 64 + g * 8, rsb + OFF_MB + MB_QX * 8, 0, 0);
            sts128(sb + OFF_TAB + 4096 + tid * 16, (uint32_t)arc, (uint32_t)(arc >> 32), snd + OFF_HP + (mt * 8 + g) * 16 + kh * 8, rsb + OFF_MB + MB_HX * 8);
            sts128(sb + OFF_TAB + 8192 + tid * 16, (uint32_t)op, (uint32_t)(op >> 32), sb + OFF_XF + (ln * 16 + cc) * 2,
                   sb + OFF_W1 + ((lane >> 3) & 1) * 16384 + (kh * 128 + (lane >> 4) * 8 + (lane & 7)) * 64 + ((mt ^ ((lane >> 1) & 3)) << 4));
            sts128(sb + OFF_TAB + 12288 + tid * 16, sb + OFF_PS + (w * 4 + (g >> 1)) * 16 + t * 4 + (g & 1) * 2, 0,
                   sn2 + OFF_OS + (w >> 1) * 64 + (g & 3) * 16 + (w & 1) * 8 + (g >> 2) * 4, rsb + OFF_MB + MB_OX * 8);
        }
        const uint32_t xb = __shfl_sync(0xffffffffu, sb + ((g & 1) ? OFF_ONE : OFF_XS) + t * 16, lane);
        const uint32_t mg = __shfl_sync(0xffffffffu, sb + t * 16 + (g & 1) * 64, lane);
        const uint32_t tab = __shfl_sync(0xffffffffu, sb + OFF_TAB + tid * 16, lane);
        const uint32_t lm = __shfl_sync(0xffffffffu, sb + ((lane >> 4) * 8 + (lane & 7)) * 128 + ((((w & 3) * 2 + ((lane >> 3) & 1)) ^ (lane & 7)) << 4), lane);
        const uint32_t wh = w >> 2;
        asm volatile("barrier.cluster.wait.acquire.aligned;" ::: "memory");
        mbar_wait(mb + MB_K * 8);
        {
            const uint32_t kp = sb + OFF_WO + (w * 32 + g) * 256 + t * 16;
#pragma unroll
            for (int rr = 0; rr < 4; rr++)
#pragma unroll
                for (int i = 0; i < 4; i++) {
                    const uint4 v = lds128(kp + rr * 2048 + i * 64);
                    uint32_t* d = &KR[(rr >> 1) * 32 + i * 8 + (rr & 1)];
                    d[0] = v.x; d[2] = v.y; d[4] = v.z; d[6] = v.w;
                }
        }
        __syncwarp();
        if (l0) mbar_arrive(mb + MB_KFREE * 8);
#pragma unroll
        for (int i = 0; i < 64; i++) VR[i] = 0;

#pragma unroll 1
        for (int layer = 0; layer < 2; layer++) {
            const uint32_t smode = (!t2 || layer == 0) ? (t1 ? 2u : 1u) : 0u, smode2 = t2 ? 0u : (t1 ? 2u : 1u);
            const uint32_t lm_wo = lm + OFF_WO + wh * 16384;
            mbar_wait(mb + MB_WQ * 8);
#pragma unroll
            for (int s = 0; s < 16; s++) ldsm4t(&S[s * 4], lm + OFF_WQ + wh * 32768 + s * 2048);
            const uint2 T0 = lds64(tab);
            float cv0 = 0.f, cv1 = 0.f;
            if (layer == 0) {
                const uint4 b = make_uint4(0x3F803F80u, 0x3F803F80u, 0x3F803F80u, 0x3F803F80u);
                ZACC;
#pragma unroll
                for (int i = 0; i < 4; i++) { MMA4(S, i * 16, i * 16 + 4, i * 16 + 8, i * 16 + 12, b, b); }
                cv0 = (a0[0] + a1[0]) + (a2[0] + a3[0]); cv1 = (a0[2] + a1[2]) + (a2[2] + a3[2]);
            }
            {
                bar_sync(B_X, 384);
                ZACC;
#pragma unroll
                for (int i = 0; i < 4; i++) {
                    const uint4 b = lds128(mg + OFF_XS + i * 128);
                    MMA4(S, i * 16, i * 16 + 4, i * 16 + 8, i * 16 + 12, b, b);
                }
                const float v0 = fsel(t2, cv0, (a0[0] + a1[0]) + (a2[1] + a3[1])), v1 = fsel(t2, cv1, (a0[2] + a1[2]) + (a2[3] + a3[3]));
                send_pair(T0.x, T0.y, v0, v1, smode);
                __syncwarp();
                if (l0) mbar_expect(mb + MB_QX * 8, layer ? 64 : 128);
            }
            STAGE_WO(0, 4);
            const uint4 T3 = lds128(tab + 12288);
            {
                bar_sync(B_Q, 288);
                uint4 b0 = lds128(mg + OFF_QS), b1;
                { const uint2 v = lds64(mg + OFF_QS + 128); b1.x = v.x; b1.y = v.y; }
                STAGE_WO(4, 8);
                __syncwarp();
                { const uint2 v = lds64(mg + OFF_QS + 136); b1.z = v.x; b1.w = v.y; }
                ZACC;
#define SC4(o, x, y) \
                mma16(a0, KR[o], KR[o + 1], KR[o + 2], KR[o + 3], x, y); mma16(a1, KR[o + 8], KR[o + 9], KR[o + 10], KR[o + 11], x, y); \
                mma16(a2, KR[o + 32], KR[o + 33], KR[o + 34], KR[o + 35], x, y); mma16(a3, KR[o + 40], KR[o + 41], KR[o + 42], KR[o + 43], x, y)
                SC4(0, b0.x, b0.y); SC4(4, b0.z, b0.w); SC4(16, b1.x, b1.y); SC4(20, b1.z, b1.w);
                const float sv = (fsel(t2, fsel(t1, a2[2], a2[0]), fsel(t1, a0[2], a0[0])) + fsel(t2, fsel(t1, a3[3], a3[1]), fsel(t1, a1[3], a1[1]))) *
                                 (0.08838834764831845f * 1.4426950408889634f);
                const float m = warp_max(sv);
                sts16(T3.x, pack_bf16(ex2(sv - m), 0.f));
                if (l0) sts32(sb + OFF_MS + w * 4, __float_as_uint(m));
            }
            bar_sync(B_S, 320);
            if (layer == 0) {
                const uint32_t vch = (w & 3) * 2 + (g >> 2), vb = sb + OFF_V + wh * 8192 + t * 256 + (g & 3) * 4;
                const uint32_t va0 = vb + ((vch ^ (2 * t)) << 4), va1 = vb + 128 + ((vch ^ (2 * t + 1)) << 4);
#pragma unroll
                for (int q = 0; q < 4; q++) {
                    mbar_wait(mb + (MB_V0 + q) * 8);
#pragma unroll
                    for (int s = 0; s < 8; s++) {
                        const uint32_t e = lds32(va0 + q * 16384 + s * 1024), o = lds32(va1 + q * 16384 + s * 1024);
                        VR[q * 16 + s * 2] = __byte_perm(e, o, 0x5410); VR[q * 16 + s * 2 + 1] = __byte_perm(e, o, 0x7632);
                    }
                    if (q == 2) {
                        __syncwarp();
                        if (l0) mbar_arrive(mb + MB_VFREE * 8);
                    }
                }
            }
            {
                uint4 b[4];
#pragma unroll
                for (int i = 0; i < 4; i++) b[i] = lds128(mg + OFF_PS + i * 128);
                __syncwarp();
                uint4 ua = lds128v(sb + OFF_MS + 32), ub = lds128v(sb + OFF_MS + 48);
                const uint32_t sgn = (uint32_t)layer << 31;
#define W_OK __all_sync(0xffffffffu, (int)((((ua.x ^ sgn) | (ua.y ^ sgn)) | ((ua.z ^ sgn) | (ua.w ^ sgn))) | (((ub.x ^ sgn) | (ub.y ^ sgn)) | ((ub.z ^ sgn) | (ub.w ^ sgn)))) >= 0)
                const bool wok = W_OK;
                float ac[8][4];
#pragma unroll
                for (int i = 0; i < 8; i++) { ac[i][0] = 0.f; ac[i][1] = 0.f; ac[i][2] = 0.f; ac[i][3] = 0.f; }
#pragma unroll
                for (int hf = 0; hf < 2; hf++) {
#pragma unroll
                    for (int i = hf * 4; i < hf * 4 + 4; i++) mma16(ac[i], VR[i * 8], VR[i * 8 + 1], VR[i * 8 + 2], VR[i * 8 + 3], b[i >> 1].x, b[i >> 1].y);
#pragma unroll
                    for (int i = hf * 4; i < hf * 4 + 4; i++) mma16(ac[i], VR[i * 8 + 4], VR[i * 8 + 5], VR[i * 8 + 6], VR[i * 8 + 7], b[i >> 1].z, b[i >> 1].w);
                }
                if (!wok) {
#pragma unroll 1
                    for (int it = 0; it < (1 << 22); it++) {
                        ua = lds128v(sb + OFF_MS + 32); ub = lds128v(sb + OFF_MS + 48);
                        if (W_OK) break;
                    }
                }
                const float4 wa = make_float4(fabsf(__uint_as_float(ua.x)), fabsf(__uint_as_float(ua.y)), fabsf(__uint_as_float(ua.z)), fabsf(__uint_as_float(ua.w)));
                const float4 wb = make_float4(fabsf(__uint_as_float(ub.x)), fabsf(__uint_as_float(ub.y)), fabsf(__uint_as_float(ub.z)), fabsf(__uint_as_float(ub.w)));
                const float ol = (fmaf(wa.x, ac[0][0], wa.y * ac[1][1]) + fmaf(wa.z, ac[2][0], wa.w * ac[3][1])) + (fmaf(wb.x, ac[4][0], wb.y * ac[5][1]) + fmaf(wb.z, ac[6][0], wb.w * ac[7][1]));
                const float oh = (fmaf(wa.x, ac[0][2], wa.y * ac[1][3]) + fmaf(wa.z, ac[2][2], wa.w * ac[3][3])) + (fmaf(wb.x, ac[4][2], wb.y * ac[5][3]) + fmaf(wb.z, ac[6][2], wb.w * ac[7][3]));
                send_word(T3.z, T3.w, pack_bf16(ol, oh), smode2);
                __syncwarp();
                if (l0) mbar_expect(mb + MB_OX * 8, 32);
            }
            STAGE_WO(8, 14);
            const uint4 T1 = lds128(tab + 4096);
            {
                mbar_wait(mb + MB_OX * 8, layer);
                uint4 b[4], ph;
                bool pok;
                ZACC;
                if (layer == 0) {
                    ph = lds128v(sb + OFF_PHI);
                    pok = __all_sync(0xffffffffu, ph.z == 1u);
#pragma unroll
                    for (int i = 0; i < 4; i++) {
                        b[0] = lds128(xb + (OFF_OS - OFF_XS) + i * 64);
                        mbar_wait(mb + (MB_WO0 + i) * 8);
                        ldsm4t(&S[0], lm_wo + i * 4096); ldsm4t(&S[4], lm_wo + i * 4096 + 2048);
                        ldsm4t(&S[8], lm_wo + 32768 + i * 4096); ldsm4t(&S[12], lm_wo + 32768 + i * 4096 + 2048);
                        MMA4(S, 0, 4, 8, 12, b[0], b[0]);
                    }
                } else {
#pragma unroll
                    for (int i = 0; i < 4; i++) b[i] = lds128(xb + (OFF_OS - OFF_XS) + i * 64);
                    STAGE_WO(14, 16);
                    __syncwarp();
                    ph = lds128v(sb + OFF_PHI);
                    pok = __all_sync(0xffffffffu, ph.z == 2u);
#pragma unroll
                    for (int i = 0; i < 4; i++) { MMA4(S, i * 8, i * 8 + 4, 32 + i * 8, 32 + i * 8 + 4, b[i], b[i]); }
                }
                if (!pok) {
#pragma unroll 1
                    for (int it = 0; it < (1 << 22); it++) {
                        ph = lds128v(sb + OFF_PHI);
                        if (__all_sync(0xffffffffu, ph.z == (uint32_t)layer + 1)) break;
                    }
                }
                red_pair(mk64(T1.x, T1.y) + layer * 512, fmaf(__uint_as_float(ph.x), PICK4C(0), __uint_as_float(ph.y) * PICK4C(1)), 1);
                bar_arrive(B_RED, 384);
            }
            if (!ffn) continue;
            const uint32_t w2a = lm + OFF_W2 + wh * 4096;
            const uint4 T2 = lds128(tab + 8192);
            {
                ldsm4t(&S[32], w2a); ldsm4t(&S[36], w2a + 2048); ldsm4t(&S[40], w2a + 8192); ldsm4t(&S[44], w2a + 8192 + 2048);
                mbar_wait(mb + (MB_W130 + wh) * 8);
#pragma unroll
                for (int s = 0; s < 8; s++) ldsm4t(&S[s * 4], T2.w + s * 1024);
                bar_sync(B_X, 384);
                ZACC;
#pragma unroll
                for (int i = 0; i < 2; i++) {
                    const uint4 b = lds128(xb + wh * 256 + i * 128), d = lds128(xb + wh * 256 + i * 128 + 64);
                    MMA4(S, i * 16, i * 16 + 4, i * 16 + 8, i * 16 + 12, b, d);
                }
                const float v0 = (fsel(t2, a0[1], a0[0]) + fsel(t2, a1[1], a1[0])) + (fsel(t2, a2[1], a2[0]) + fsel(t2, a3[1], a3[0]));
                const float v1 = (fsel(t2, a0[3], a0[2]) + fsel(t2, a1[3], a1[2])) + (fsel(t2, a2[3], a2[2]) + fsel(t2, a3[3], a3[2]));
                send_pair(T1.z, T1.w, v0, v1, smode);
                __syncwarp();
                if (l0) mbar_expect(mb + MB_HX * 8, layer ? 64 : 128);
            }
            if (layer == 0) {
                mbar_wait(mb + MB_W2 * 8);
                ldsm4t(&S[32], w2a); ldsm4t(&S[36], w2a + 2048); ldsm4t(&S[40], w2a + 8192); ldsm4t(&S[44], w2a + 8192 + 2048);
            }
            {
                uint16_t xr; asm volatile("ld.shared.u16 %0, [%1];" : "=h"(xr) : "r"(T2.z) : "memory");
                const uint32_t epoch = lds32(sb + OFF_EP);
                bar_sync(B_H, 288);
                const uint4 b = lds128(xb + (OFF_HS - OFF_XS));
                ZACC;
                MMA4(S, 32, 36, 40, 44, b, b);
                const float v = PICK4;
                if (layer == 0) {
                    red_pair(mk64(T1.x, T1.y) + 128, v, 1);
                    bar_arrive(B_RED, 384);
                } else {
                    float ov, oc;
                    asm volatile("atom.relaxed.gpu.global.add.v2.f32 {%0,%1}, [%2], {%3,%4};" : "=f"(ov), "=f"(oc) : "l"(mk64(T1.x, T1.y) + 640), "f"(v), "f"(1.f) : "memory");
                    if (oc == (float)(kNFFN - 1)) {
                        const float y = __uint_as_float((uint32_t)xr << 16) + bf_lo(pack_bf16(ov + v, 0.f));
                        asm volatile("st.global.u16 [%0], %1;" :: "l"(mk64(T2.x, T2.y)), "h"((uint16_t)pack_bf16(y, 0.f)) : "memory");
                        if (r == 0 && w == 0 && l0) asm volatile("st.relaxed.gpu.global.u32 [%0], %1;" :: "l"(g_epoch_line), "r"(epoch + 1) : "memory");
                    }
                }
            }
        }
    }
}

__device__ __forceinline__ float bfr(float v) { return __bfloat162float(__float2bfloat16(v)); }
__global__ void fb_ln(const __nv_bfloat16* x0, int first) {
    __shared__ float red[2][16];
    const int tid = threadIdx.x;
    float x = first ? __bfloat162float(x0[tid]) : g_fb[tid];
    g_fb[tid] = x;
    float s = x;
    for (int o = 16; o > 0; o >>= 1) s += __shfl_xor_sync(0xffffffffu, s, o);
    if ((tid & 31) == 0) red[0][tid >> 5] = s;
    __syncthreads();
    float m = 0.f;
    for (int i = 0; i < 16; i++) m += red[0][i];
    m *= 1.f / kD;
    float d = (x - m) * (x - m);
    for (int o = 16; o > 0; o >>= 1) d += __shfl_xor_sync(0xffffffffu, d, o);
    if ((tid & 31) == 0) red[1][tid >> 5] = d;
    __syncthreads();
    float v = 0.f;
    for (int i = 0; i < 16; i++) v += red[1][i];
    g_fb[512 + tid] = (x - m) * rsqrtf(v * (1.f / kD) + 1e-5f);
}
__global__ void fb_attn(const __nv_bfloat16* kc, const __nv_bfloat16* vc, const __nv_bfloat16* wq) {
    __shared__ float q[128], s[1024], red[32];
    const int h = blockIdx.x, tid = threadIdx.x;
    if (tid < 128) {
        float a = 0.f;
        for (int d = 0; d < kD; d++) a += g_fb[512 + d] * __bfloat162float(wq[(size_t)d * 4096 + h * 128 + tid]);
        q[tid] = bfr(a);
    }
    __syncthreads();
    const __nv_bfloat16* kr = kc + ((size_t)h * kSK + (kSK - kW) + tid) * kDH;
    float a = 0.f;
    for (int d = 0; d < kDH; d++) a += q[d] * __bfloat162float(kr[d]);
    a *= 0.08838834764831845f;
    float m = a;
    for (int o = 16; o > 0; o >>= 1) m = fmaxf(m, __shfl_xor_sync(0xffffffffu, m, o));
    if ((tid & 31) == 0) red[tid >> 5] = m;
    __syncthreads();
    for (int i = 0; i < 32; i++) m = fmaxf(m, red[i]);
    __syncthreads();
    const float e = expf(a - m);
    s[tid] = e;
    float l = e;
    for (int o = 16; o > 0; o >>= 1) l += __shfl_xor_sync(0xffffffffu, l, o);
    if ((tid & 31) == 0) red[tid >> 5] = l;
    __syncthreads();
    l = 0.f;
    for (int i = 0; i < 32; i++) l += red[i];
    if (tid < 128) {
        float o = 0.f;
        const __nv_bfloat16* vr = vc + ((size_t)h * kSK + (kSK - kW)) * kDH + tid;
        for (int k = 0; k < kW; k++) o += s[k] * __bfloat162float(vr[(size_t)k * kDH]);
        g_fb[1024 + h * 128 + tid] = bfr(o / l);
    }
}
__global__ void fb_up(const __nv_bfloat16* w1, const __nv_bfloat16* w3) {
    const int f = blockIdx.x * blockDim.x + threadIdx.x;
    if (f >= kF) return;
    float a = 0.f, b = 0.f;
    for (int d = 0; d < kD; d++) { a += g_fb[512 + d] * __bfloat162float(w1[(size_t)d * kF + f]); b += g_fb[512 + d] * __bfloat162float(w3[(size_t)d * kF + f]); }
    g_fb[5120 + f] = bfr(a / (1.f + expf(-a)) * b);
}
__global__ void fb_down(const __nv_bfloat16* w, int src, int n, __nv_bfloat16* out) {
    const int col = blockIdx.x * blockDim.x + threadIdx.x;
    float a = 0.f;
    for (int k = 0; k < n; k++) a += g_fb[src + k] * __bfloat162float(w[(size_t)k * kD + col]);
    const float y = bfr(g_fb[col] + bfr(a));
    g_fb[col] = y;
    if (out) out[col] = __float2bfloat16(y);
}

typedef CUresult (*EncodeFn)(CUtensorMap*, CUtensorMapDataType, cuuint32_t, void*, const cuuint64_t*, const cuuint64_t*,
                             const cuuint32_t*, const cuuint32_t*, CUtensorMapInterleave, CUtensorMapSwizzle,
                             CUtensorMapL2promotion, CUtensorMapFloatOOBfill);

bool make_map(EncodeFn fn, CUtensorMap* m, const void* base, uint64_t cols, uint64_t rows, uint32_t bc, uint32_t br, CUtensorMapSwizzle swz) {
    cuuint64_t dims[2] = {cols, rows};
    cuuint64_t strides[1] = {cols * 2};
    cuuint32_t box[2] = {bc, br};
    cuuint32_t es[2] = {1, 1};
    return fn(m, CU_TENSOR_MAP_DATA_TYPE_BFLOAT16, 2, const_cast<void*>(base), dims, strides, box, es, CU_TENSOR_MAP_INTERLEAVE_NONE,
              swz, CU_TENSOR_MAP_L2_PROMOTION_NONE, CU_TENSOR_MAP_FLOAT_OOB_FILL_NONE) == CUDA_SUCCESS;
}

Sched g_sched = {{2140, 2590, 2940, 3190, 3490, 3990, 4690, 5390, 6110, 6420, 6760, 7100, 7690, 8190, 8790, 0},
                 {150, 350, 250, 250, 380, 300, 150, 0}};

}

extern "C" void kernel_launch(void* const* d_in, const int* in_sizes, int n_in, void* d_out, int out_size) {
    (void)in_sizes; (void)n_in; (void)out_size;
    const __nv_bfloat16* x0 = (const __nv_bfloat16*)d_in[0];
    const __nv_bfloat16* kc = (const __nv_bfloat16*)d_in[1];
    const __nv_bfloat16* vc = (const __nv_bfloat16*)d_in[2];
    const __nv_bfloat16* wq = (const __nv_bfloat16*)d_in[3];
    const __nv_bfloat16* wo = (const __nv_bfloat16*)d_in[4];
    const __nv_bfloat16* w1 = (const __nv_bfloat16*)d_in[6];
    const __nv_bfloat16* w3 = (const __nv_bfloat16*)d_in[7];
    const __nv_bfloat16* w2 = (const __nv_bfloat16*)d_in[8];
    __nv_bfloat16* out = (__nv_bfloat16*)d_out;
    cudaStream_t s = cudaStreamPerThread;

    static int state = 0;
    static EncodeFn enc = nullptr;
    if (state == 0) {
        state = 2;
        void* fn = nullptr;
        cudaDriverEntryPointQueryResult qr;
        if (cudaGetDriverEntryPoint("cuTensorMapEncodeTiled", &fn, cudaEnableDefault, &qr) == cudaSuccess && fn &&
            cudaFuncSetAttribute(fused_kernel, cudaFuncAttributeMaxDynamicSharedMemorySize, SMEM_BYTES) == cudaSuccess) {
            enc = (EncodeFn)fn;
            cudaLaunchConfig_t cfg = {};
            cfg.gridDim = dim3(kNCTA); cfg.blockDim = dim3(kNTHR); cfg.dynamicSmemBytes = SMEM_BYTES;
            cudaLaunchAttribute at[1];
            at[0].id = cudaLaunchAttributeClusterDimension;
            at[0].val.clusterDim.x = 2; at[0].val.clusterDim.y = 1; at[0].val.clusterDim.z = 1;
            cfg.attrs = at; cfg.numAttrs = 1;
            int ncl = 0;
            if (cudaOccupancyMaxActiveClusters(&ncl, fused_kernel, &cfg) == cudaSuccess && ncl >= kNCTA / 2) state = 1;
        }
        (void)cudaGetLastError();
    }
    if (state == 1) {
        Maps tm;
        bool ok = make_map(enc, &tm.m[0], wq, 4096, 512, 64, 64, CU_TENSOR_MAP_SWIZZLE_128B) &&
                  make_map(enc, &tm.m[1], vc, 128, (uint64_t)kHQ * kSK, 64, 64, CU_TENSOR_MAP_SWIZZLE_128B) &&
                  make_map(enc, &tm.m[2], wo, 512, 4096, 64, 32, CU_TENSOR_MAP_SWIZZLE_128B) &&
                  make_map(enc, &tm.m[3], w1, kF, 512, 32, 128, CU_TENSOR_MAP_SWIZZLE_64B) &&
                  make_map(enc, &tm.m[4], w3, kF, 512, 32, 128, CU_TENSOR_MAP_SWIZZLE_64B) &&
                  make_map(enc, &tm.m[5], w2, 512, kF, 64, 32, CU_TENSOR_MAP_SWIZZLE_128B);
        if (ok) {
            fused_kernel<<<kNCTA, kNTHR, SMEM_BYTES, s>>>(kc, x0, out, g_sched, tm);
            return;
        }
    }
    for (int layer = 0; layer < 2; layer++) {
        fb_ln<<<1, 512, 0, s>>>(x0, layer == 0);
        fb_attn<<<kHQ, 1024, 0, s>>>(kc, vc, wq);
        fb_down<<<8, 64, 0, s>>>(wo, 1024, 4096, nullptr);
        fb_ln<<<1, 512, 0, s>>>(x0, 0);
        fb_up<<<(kF + 63) / 64, 64, 0, s>>>(w1, w3);
        fb_down<<<8, 64, 0, s>>>(w2, 5120, kF, layer == 1 ? out : nullptr);
    }
}
```
